```python
import torch

def _softmax(x, axis=-1):
    return torch.softmax(x, dim=axis)
def _gelu(x):
    return torch.nn.functional.gelu(x, approximate="tanh")
def _silu(x):
    return torch.nn.functional.silu(x)
def _sigmoid(x):
    return torch.sigmoid(x)
def _layernorm(x, axis=-1, eps=1e-5):
    m = x.mean(dim=axis, keepdim=True)
    v = x.var(dim=axis, keepdim=True, unbiased=False)
    return (x - m) / torch.sqrt(v + eps)
def _scatter_add(tgt, idx, src, axis=0):
    return tgt.clone().index_add_(axis, idx, src)
def _segment_sum(src, seg, n):
    out = torch.zeros((n,) + src.shape[1:], dtype=src.dtype)
    return out.index_add_(0, seg, src)
def _pad(x, pw):
    flat = tuple(v for pair in reversed(pw) for v in pair)
    return torch.nn.functional.pad(x, flat)

kernel_name = 'standalone__mha_softmax__near_ridge'

def setup_inputs():

    _w = (lambda a: (lambda t: t.to(torch.bfloat16) if t.is_floating_point() else t)(torch.as_tensor(a)))
    B, H, Sq, Sk, D = 32, 16, 384, 384, 256
    return {
        "q": _w((lambda *s: torch.randn(*s, dtype=torch.bfloat16) * 0.8)(B, H, Sq, D)),
        "k": _w((lambda *s: torch.randn(*s, dtype=torch.bfloat16) * 0.8)(B, H, Sk, D)),
        "v": _w((lambda *s: torch.randn(*s, dtype=torch.bfloat16) * 0.05)(B, H, Sk, D)),
    }

def reference(q, k, v):
    scale = q.shape[-1] ** -0.5
    scores = torch.einsum("bhqd,bhkd->bhqk", q, k) * scale
    p = _softmax(scores, axis=-1)
    return torch.einsum("bhqk,bhkd->bhqd", p, v)
```

```cpp
#include <cuda_runtime.h>
#include <cuda_bf16.h>
#include <cuda.h>
#include <stdint.h>

#define INPLACE 0
#define TOKEN 1

namespace {

constexpr int NH = 512;
constexpr int S = 384;
constexpr int D = 256;
constexpr int NSLOT = 7;
constexpr uint32_t SLOT_BYTES = 16384;
constexpr uint32_t OFF_Q = 0;
constexpr uint32_t OFF_RING = 98304;
constexpr uint32_t OFF_STAGE = OFF_RING + NSLOT * SLOT_BYTES;
constexpr uint32_t OFF_BAR = OFF_STAGE + 12 * 1024;
constexpr uint32_t SMEM_BYTES = OFF_BAR + 256;
constexpr float SCALE_LOG2E = 0.0625f * 1.4426950408889634f;

struct Params {
    CUtensorMap q, k, v;
    __nv_bfloat16* o;
    int hotmask;
};

__device__ __forceinline__ uint32_t smem_u32(const void* p) { return (uint32_t)__cvta_generic_to_shared(p); }
__device__ __forceinline__ void mbar_init(uint32_t bar, uint32_t cnt) {
    asm volatile("mbarrier.init.shared::cta.b64 [%0], %1;" :: "r"(bar), "r"(cnt) : "memory");
}
__device__ __forceinline__ void mbar_expect_tx(uint32_t bar, uint32_t bytes) {
    asm volatile("mbarrier.arrive.expect_tx.shared::cta.b64 _, [%0], %1;" :: "r"(bar), "r"(bytes) : "memory");
}
__device__ __forceinline__ void mbar_arrive_cluster(uint32_t bar_cluster_addr, bool pred) {
    asm volatile("{\n.reg .pred p;\nsetp.ne.b32 p, %1, 0;\n@p mbarrier.arrive.shared::cluster.b64 _, [%0];\n}"
                 :: "r"(bar_cluster_addr), "r"((int)pred) : "memory");
}
__device__ __forceinline__ void mbar_wait(uint32_t bar, uint32_t parity) {
    asm volatile("{\n.reg .pred p;\n.reg .b32 n;\n"
                 "mbarrier.try_wait.parity.shared::cta.b64 p, [%0], %1;\n"
                 "@p bra DONE_%=;\n"
                 "mov.b32 n, 0;\n"
                 "WAIT_%=:\n"
                 "mbarrier.try_wait.parity.shared::cta.b64 p, [%0], %1;\n"
                 "@p bra DONE_%=;\n"
                 "add.u32 n, n, 1;\n"
                 "setp.lt.u32 p, n, 0x100000;\n"
                 "@p bra WAIT_%=;\n"
                 "trap;\n"
                 "DONE_%=:\n}"
                 :: "r"(bar), "r"(parity) : "memory");
}
__device__ __forceinline__ void tma_load(uint32_t dst, const CUtensorMap* m, uint32_t bar, int c0, int c1) {
    asm volatile("cp.async.bulk.tensor.2d.shared::cluster.global.mbarrier::complete_tx::bytes [%0], [%1, {%3, %4}], [%2];"
                 :: "r"(dst), "l"(m), "r"(bar), "r"(c0), "r"(c1) : "memory");
}
__device__ __forceinline__ void tma_load_mc(uint32_t dst, const CUtensorMap* m, uint32_t bar, int c0, int c1) {
    asm volatile("cp.async.bulk.tensor.2d.shared::cluster.global.mbarrier::complete_tx::bytes.multicast::cluster [%0], [%1, {%3, %4}], [%2], %5;"
                 :: "r"(dst), "l"(m), "r"(bar), "r"(c0), "r"(c1), "h"((uint16_t)3) : "memory");
}
__device__ __forceinline__ void wg_fence() { asm volatile("wgmma.fence.sync.aligned;" ::: "memory"); }
__device__ __forceinline__ void wg_commit() { asm volatile("wgmma.commit_group.sync.aligned;" ::: "memory"); }
template <int N> __device__ __forceinline__ void wg_wait() { asm volatile("wgmma.wait_group.sync.aligned %0;" :: "n"(N) : "memory"); }
template <int N> __device__ __forceinline__ void fence_regs(float (&d)[N]) {
#pragma unroll
    for (int i = 0; i < N; i++) asm volatile("" : "+f"(d[i]) :: "memory");
}
__device__ __forceinline__ void sched_fence(uint32_t x) {
    asm volatile("{\n.reg .pred p;\nsetp.ne.u32 p, %0, 0xdeadbeef;\n@p bra OK_%=;\ntrap;\nOK_%=:\n}" :: "r"(x) : "memory");
}
__device__ __forceinline__ float ex2(float x) { float y; asm("ex2.approx.ftz.f32 %0, %1;" : "=f"(y) : "f"(x)); return y; }
__device__ __forceinline__ uint32_t pack_bf16(float lo, float hi) {
    uint32_t r; asm("cvt.rn.bf16x2.f32 %0, %1, %2;" : "=r"(r) : "f"(hi), "f"(lo)); return r;
}
__device__ __forceinline__ void scale_bf16x2(uint32_t& a, uint32_t b) {
    uint32_t r; asm("mul.rn.bf16x2 %0, %1, %2;" : "=r"(r) : "r"(a), "r"(b)); a = r;
}
__device__ __forceinline__ void exp4(float s0, float s1, float s2, float s3, float m0, float m1,
                                     uint32_t& p0, uint32_t& p1, float& a0, float& a1) {
    asm volatile("{\n.reg .f32 t0, t1, t2, t3;\n"
                 "fma.rn.f32 t0, %4, %10, %8;\nfma.rn.f32 t1, %5, %10, %8;\n"
                 "fma.rn.f32 t2, %6, %10, %9;\nfma.rn.f32 t3, %7, %10, %9;\n"
                 "ex2.approx.ftz.f32 t0, t0;\nex2.approx.ftz.f32 t1, t1;\n"
                 "ex2.approx.ftz.f32 t2, t2;\nex2.approx.ftz.f32 t3, t3;\n"
                 "cvt.rn.bf16x2.f32 %0, t1, t0;\ncvt.rn.bf16x2.f32 %1, t3, t2;\n"
                 "add.f32 t0, t0, t1;\nadd.f32 t2, t2, t3;\n"
                 "add.f32 %2, %2, t0;\nadd.f32 %3, %3, t2;\n}"
                 : "=r"(p0), "=r"(p1), "+f"(a0), "+f"(a1)
                 : "f"(s0), "f"(s1), "f"(s2), "f"(s3), "f"(-m0), "f"(-m1), "f"(SCALE_LOG2E));
}
__device__ __forceinline__ uint32_t desc_lo(uint32_t addr) { return ((addr >> 4) & 0x3FFF) | (1u << 16); }
__device__ __forceinline__ void qk_group_init(float (&d)[64], uint32_t a_lo, uint32_t b_lo) {
    asm volatile("{\n.reg .b64 da, db;\n.reg .b32 a, b;\n"
        "wgmma.fence.sync.aligned;\n"
        "add.u32 a, %64, 0;\nadd.u32 b, %65, 0;\nmov.b64 da, {a, 0x40000040};\nmov.b64 db, {b, 0x40000040};\n"
        "wgmma.mma_async.sync.aligned.m64n128k16.f32.bf16.bf16 {%0, %1, %2, %3, %4, %5, %6, %7, %8, %9, %10, %11, %12, "
        "%13, %14, %15, %16, %17, %18, %19, %20, %21, %22, %23, %24, %25, %26, %27, %28, %29, %30, %31, %32, %33, %34, "
        "%35, %36, %37, %38, %39, %40, %41, %42, %43, %44, %45, %46, %47, %48, %49, %50, %51, %52, %53, %54, %55, %56, "
        "%57, %58, %59, %60, %61, %62, %63}, da, db, 0, 1, 1, 0, 0;\n"
        "add.u32 a, %64, 2;\nadd.u32 b, %65, 2;\nmov.b64 da, {a, 0x40000040};\nmov.b64 db, {b, 0x40000040};\n"
        "wgmma.mma_async.sync.aligned.m64n128k16.f32.bf16.bf16 {%0, %1, %2, %3, %4, %5, %6, %7, %8, %9, %10, %11, %12, "
        "%13, %14, %15, %16, %17, %18, %19, %20, %21, %22, %23, %24, %25, %26, %27, %28, %29, %30, %31, %32, %33, %34, "
        "%35, %36, %37, %38, %39, %40, %41, %42, %43, %44, %45, %46, %47, %48, %49, %50, %51, %52, %53, %54, %55, %56, "
        "%57, %58, %59, %60, %61, %62, %63}, da, db, 1, 1, 1, 0, 0;\n"
        "add.u32 a, %64, 4;\nadd.u32 b, %65, 4;\nmov.b64 da, {a, 0x40000040};\nmov.b64 db, {b, 0x40000040};\n"
        "wgmma.mma_async.sync.aligned.m64n128k16.f32.bf16.bf16 {%0, %1, %2, %3, %4, %5, %6, %7, %8, %9, %10, %11, %12, "
        "%13, %14, %15, %16, %17, %18, %19, %20, %21, %22, %23, %24, %25, %26, %27, %28, %29, %30, %31, %32, %33, %34, "
        "%35, %36, %37, %38, %39, %40, %41, %42, %43, %44, %45, %46, %47, %48, %49, %50, %51, %52, %53, %54, %55, %56, "
        "%57, %58, %59, %60, %61, %62, %63}, da, db, 1, 1, 1, 0, 0;\n"
        "add.u32 a, %64, 6;\nadd.u32 b, %65, 6;\nmov.b64 da, {a, 0x40000040};\nmov.b64 db, {b, 0x40000040};\n"
        "wgmma.mma_async.sync.aligned.m64n128k16.f32.bf16.bf16 {%0, %1, %2, %3, %4, %5, %6, %7, %8, %9, %10, %11, %12, "
        "%13, %14, %15, %16, %17, %18, %19, %20, %21, %22, %23, %24, %25, %26, %27, %28, %29, %30, %31, %32, %33, %34, "
        "%35, %36, %37, %38, %39, %40, %41, %42, %43, %44, %45, %46, %47, %48, %49, %50, %51, %52, %53, %54, %55, %56, "
        "%57, %58, %59, %60, %61, %62, %63}, da, db, 1, 1, 1, 0, 0;\n"
        "wgmma.commit_group.sync.aligned;\n}"
        : "=f"(d[0]), "=f"(d[1]), "=f"(d[2]), "=f"(d[3]), "=f"(d[4]), "=f"(d[5]), "=f"(d[6]), "=f"(d[7]),
          "=f"(d[8]), "=f"(d[9]), "=f"(d[10]), "=f"(d[11]), "=f"(d[12]), "=f"(d[13]), "=f"(d[14]), "=f"(d[15]),
          "=f"(d[16]), "=f"(d[17]), "=f"(d[18]), "=f"(d[19]), "=f"(d[20]), "=f"(d[21]), "=f"(d[22]), "=f"(d[23]),
          "=f"(d[24]), "=f"(d[25]), "=f"(d[26]), "=f"(d[27]), "=f"(d[28]), "=f"(d[29]), "=f"(d[30]), "=f"(d[31]),
          "=f"(d[32]), "=f"(d[33]), "=f"(d[34]), "=f"(d[35]), "=f"(d[36]), "=f"(d[37]), "=f"(d[38]), "=f"(d[39]),
          "=f"(d[40]), "=f"(d[41]), "=f"(d[42]), "=f"(d[43]), "=f"(d[44]), "=f"(d[45]), "=f"(d[46]), "=f"(d[47]),
          "=f"(d[48]), "=f"(d[49]), "=f"(d[50]), "=f"(d[51]), "=f"(d[52]), "=f"(d[53]), "=f"(d[54]), "=f"(d[55]),
          "=f"(d[56]), "=f"(d[57]), "=f"(d[58]), "=f"(d[59]), "=f"(d[60]), "=f"(d[61]), "=f"(d[62]), "=f"(d[63])
        : "r"(a_lo), "r"(b_lo) : "memory");
}
__device__ __forceinline__ void qk_group_acc(float (&d)[64], uint32_t a_lo, uint32_t b_lo) {
    asm volatile("{\n.reg .b64 da, db;\n.reg .b32 a, b;\n"
        "wgmma.fence.sync.aligned;\n"
        "add.u32 a, %64, 0;\nadd.u32 b, %65, 0;\nmov.b64 da, {a, 0x40000040};\nmov.b64 db, {b, 0x40000040};\n"
        "wgmma.mma_async.sync.aligned.m64n128k16.f32.bf16.bf16 {%0, %1, %2, %3, %4, %5, %6, %7, %8, %9, %10, %11, %12, "
        "%13, %14, %15, %16, %17, %18, %19, %20, %21, %22, %23, %24, %25, %26, %27, %28, %29, %30, %31, %32, %33, %34, "
        "%35, %36, %37, %38, %39, %40, %41, %42, %43, %44, %45, %46, %47, %48, %49, %50, %51, %52, %53, %54, %55, %56, "
        "%57, %58, %59, %60, %61, %62, %63}, da, db, 1, 1, 1, 0, 0;\n"
        "add.u32 a, %64, 2;\nadd.u32 b, %65, 2;\nmov.b64 da, {a, 0x40000040};\nmov.b64 db, {b, 0x40000040};\n"
        "wgmma.mma_async.sync.aligned.m64n128k16.f32.bf16.bf16 {%0, %1, %2, %3, %4, %5, %6, %7, %8, %9, %10, %11, %12, "
        "%13, %14, %15, %16, %17, %18, %19, %20, %21, %22, %23, %24, %25, %26, %27, %28, %29, %30, %31, %32, %33, %34, "
        "%35, %36, %37, %38, %39, %40, %41, %42, %43, %44, %45, %46, %47, %48, %49, %50, %51, %52, %53, %54, %55, %56, "
        "%57, %58, %59, %60, %61, %62, %63}, da, db, 1, 1, 1, 0, 0;\n"
        "add.u32 a, %64, 4;\nadd.u32 b, %65, 4;\nmov.b64 da, {a, 0x40000040};\nmov.b64 db, {b, 0x40000040};\n"
        "wgmma.mma_async.sync.aligned.m64n128k16.f32.bf16.bf16 {%0, %1, %2, %3, %4, %5, %6, %7, %8, %9, %10, %11, %12, "
        "%13, %14, %15, %16, %17, %18, %19, %20, %21, %22, %23, %24, %25, %26, %27, %28, %29, %30, %31, %32, %33, %34, "
        "%35, %36, %37, %38, %39, %40, %41, %42, %43, %44, %45, %46, %47, %48, %49, %50, %51, %52, %53, %54, %55, %56, "
        "%57, %58, %59, %60, %61, %62, %63}, da, db, 1, 1, 1, 0, 0;\n"
        "add.u32 a, %64, 6;\nadd.u32 b, %65, 6;\nmov.b64 da, {a, 0x40000040};\nmov.b64 db, {b, 0x40000040};\n"
        "wgmma.mma_async.sync.aligned.m64n128k16.f32.bf16.bf16 {%0, %1, %2, %3, %4, %5, %6, %7, %8, %9, %10, %11, %12, "
        "%13, %14, %15, %16, %17, %18, %19, %20, %21, %22, %23, %24, %25, %26, %27, %28, %29, %30, %31, %32, %33, %34, "
        "%35, %36, %37, %38, %39, %40, %41, %42, %43, %44, %45, %46, %47, %48, %49, %50, %51, %52, %53, %54, %55, %56, "
        "%57, %58, %59, %60, %61, %62, %63}, da, db, 1, 1, 1, 0, 0;\n"
        "wgmma.commit_group.sync.aligned;\n}"
        : "+f"(d[0]), "+f"(d[1]), "+f"(d[2]), "+f"(d[3]), "+f"(d[4]), "+f"(d[5]), "+f"(d[6]), "+f"(d[7]),
          "+f"(d[8]), "+f"(d[9]), "+f"(d[10]), "+f"(d[11]), "+f"(d[12]), "+f"(d[13]), "+f"(d[14]), "+f"(d[15]),
          "+f"(d[16]), "+f"(d[17]), "+f"(d[18]), "+f"(d[19]), "+f"(d[20]), "+f"(d[21]), "+f"(d[22]), "+f"(d[23]),
          "+f"(d[24]), "+f"(d[25]), "+f"(d[26]), "+f"(d[27]), "+f"(d[28]), "+f"(d[29]), "+f"(d[30]), "+f"(d[31]),
          "+f"(d[32]), "+f"(d[33]), "+f"(d[34]), "+f"(d[35]), "+f"(d[36]), "+f"(d[37]), "+f"(d[38]), "+f"(d[39]),
          "+f"(d[40]), "+f"(d[41]), "+f"(d[42]), "+f"(d[43]), "+f"(d[44]), "+f"(d[45]), "+f"(d[46]), "+f"(d[47]),
          "+f"(d[48]), "+f"(d[49]), "+f"(d[50]), "+f"(d[51]), "+f"(d[52]), "+f"(d[53]), "+f"(d[54]), "+f"(d[55]),
          "+f"(d[56]), "+f"(d[57]), "+f"(d[58]), "+f"(d[59]), "+f"(d[60]), "+f"(d[61]), "+f"(d[62]), "+f"(d[63])
        : "r"(a_lo), "r"(b_lo) : "memory");
}
__device__ __forceinline__ void pv_group_init(float (&d)[32], const uint32_t* a, uint32_t b_lo) {
    asm volatile("{\n.reg .b64 db;\n.reg .b32 b;\n"
        "wgmma.fence.sync.aligned;\n"
        "add.u32 b, %64, 0;\nmov.b64 db, {b, 0x40000040};\n"
        "wgmma.mma_async.sync.aligned.m64n64k16.f32.bf16.bf16 {%0, %1, %2, %3, %4, %5, %6, %7, %8, %9, %10, %11, %12, "
        "%13, %14, %15, %16, %17, %18, %19, %20, %21, %22, %23, %24, %25, %26, %27, %28, %29, %30, %31}, {%32, %33, "
        "%34, %35}, db, 0, 1, 1, 1;\n"
        "add.u32 b, %64, 128;\nmov.b64 db, {b, 0x40000040};\n"
        "wgmma.mma_async.sync.aligned.m64n64k16.f32.bf16.bf16 {%0, %1, %2, %3, %4, %5, %6, %7, %8, %9, %10, %11, %12, "
        "%13, %14, %15, %16, %17, %18, %19, %20, %21, %22, %23, %24, %25, %26, %27, %28, %29, %30, %31}, {%36, %37, "
        "%38, %39}, db, 1, 1, 1, 1;\n"
        "add.u32 b, %64, 256;\nmov.b64 db, {b, 0x40000040};\n"
        "wgmma.mma_async.sync.aligned.m64n64k16.f32.bf16.bf16 {%0, %1, %2, %3, %4, %5, %6, %7, %8, %9, %10, %11, %12, "
        "%13, %14, %15, %16, %17, %18, %19, %20, %21, %22, %23, %24, %25, %26, %27, %28, %29, %30, %31}, {%40, %41, "
        "%42, %43}, db, 1, 1, 1, 1;\n"
        "add.u32 b, %64, 384;\nmov.b64 db, {b, 0x40000040};\n"
        "wgmma.mma_async.sync.aligned.m64n64k16.f32.bf16.bf16 {%0, %1, %2, %3, %4, %5, %6, %7, %8, %9, %10, %11, %12, "
        "%13, %14, %15, %16, %17, %18, %19, %20, %21, %22, %23, %24, %25, %26, %27, %28, %29, %30, %31}, {%44, %45, "
        "%46, %47}, db, 1, 1, 1, 1;\n"
        "add.u32 b, %64, 512;\nmov.b64 db, {b, 0x40000040};\n"
        "wgmma.mma_async.sync.aligned.m64n64k16.f32.bf16.bf16 {%0, %1, %2, %3, %4, %5, %6, %7, %8, %9, %10, %11, %12, "
        "%13, %14, %15, %16, %17, %18, %19, %20, %21, %22, %23, %24, %25, %26, %27, %28, %29, %30, %31}, {%48, %49, "
        "%50, %51}, db, 1, 1, 1, 1;\n"
        "add.u32 b, %64, 640;\nmov.b64 db, {b, 0x40000040};\n"
        "wgmma.mma_async.sync.aligned.m64n64k16.f32.bf16.bf16 {%0, %1, %2, %3, %4, %5, %6, %7, %8, %9, %10, %11, %12, "
        "%13, %14, %15, %16, %17, %18, %19, %20, %21, %22, %23, %24, %25, %26, %27, %28, %29, %30, %31}, {%52, %53, "
        "%54, %55}, db, 1, 1, 1, 1;\n"
        "add.u32 b, %64, 768;\nmov.b64 db, {b, 0x40000040};\n"
        "wgmma.mma_async.sync.aligned.m64n64k16.f32.bf16.bf16 {%0, %1, %2, %3, %4, %5, %6, %7, %8, %9, %10, %11, %12, "
        "%13, %14, %15, %16, %17, %18, %19, %20, %21, %22, %23, %24, %25, %26, %27, %28, %29, %30, %31}, {%56, %57, "
        "%58, %59}, db, 1, 1, 1, 1;\n"
        "add.u32 b, %64, 896;\nmov.b64 db, {b, 0x40000040};\n"
        "wgmma.mma_async.sync.aligned.m64n64k16.f32.bf16.bf16 {%0, %1, %2, %3, %4, %5, %6, %7, %8, %9, %10, %11, %12, "
        "%13, %14, %15, %16, %17, %18, %19, %20, %21, %22, %23, %24, %25, %26, %27, %28, %29, %30, %31}, {%60, %61, "
        "%62, %63}, db, 1, 1, 1, 1;\n"
        "wgmma.commit_group.sync.aligned;\n}"
        : "=f"(d[0]), "=f"(d[1]), "=f"(d[2]), "=f"(d[3]), "=f"(d[4]), "=f"(d[5]), "=f"(d[6]), "=f"(d[7]),
          "=f"(d[8]), "=f"(d[9]), "=f"(d[10]), "=f"(d[11]), "=f"(d[12]), "=f"(d[13]), "=f"(d[14]), "=f"(d[15]),
          "=f"(d[16]), "=f"(d[17]), "=f"(d[18]), "=f"(d[19]), "=f"(d[20]), "=f"(d[21]), "=f"(d[22]), "=f"(d[23]),
          "=f"(d[24]), "=f"(d[25]), "=f"(d[26]), "=f"(d[27]), "=f"(d[28]), "=f"(d[29]), "=f"(d[30]), "=f"(d[31])
        : "r"(a[0]), "r"(a[1]), "r"(a[2]), "r"(a[3]), "r"(a[4]), "r"(a[5]), "r"(a[6]), "r"(a[7]),
          "r"(a[8]), "r"(a[9]), "r"(a[10]), "r"(a[11]), "r"(a[12]), "r"(a[13]), "r"(a[14]), "r"(a[15]),
          "r"(a[16]), "r"(a[17]), "r"(a[18]), "r"(a[19]), "r"(a[20]), "r"(a[21]), "r"(a[22]), "r"(a[23]),
          "r"(a[24]), "r"(a[25]), "r"(a[26]), "r"(a[27]), "r"(a[28]), "r"(a[29]), "r"(a[30]), "r"(a[31]), "r"(b_lo) : "memory");
}
__device__ __forceinline__ void pv_group_acc(float (&d)[32], const uint32_t* a, uint32_t b_lo) {
    asm volatile("{\n.reg .b64 db;\n.reg .b32 b;\n"
        "wgmma.fence.sync.aligned;\n"
        "add.u32 b, %64, 0;\nmov.b64 db, {b, 0x40000040};\n"
        "wgmma.mma_async.sync.aligned.m64n64k16.f32.bf16.bf16 {%0, %1, %2, %3, %4, %5, %6, %7, %8, %9, %10, %11, %12, "
        "%13, %14, %15, %16, %17, %18, %19, %20, %21, %22, %23, %24, %25, %26, %27, %28, %29, %30, %31}, {%32, %33, "
        "%34, %35}, db, 1, 1, 1, 1;\n"
        "add.u32 b, %64, 128;\nmov.b64 db, {b, 0x40000040};\n"
        "wgmma.mma_async.sync.aligned.m64n64k16.f32.bf16.bf16 {%0, %1, %2, %3, %4, %5, %6, %7, %8, %9, %10, %11, %12, "
        "%13, %14, %15, %16, %17, %18, %19, %20, %21, %22, %23, %24, %25, %26, %27, %28, %29, %30, %31}, {%36, %37, "
        "%38, %39}, db, 1, 1, 1, 1;\n"
        "add.u32 b, %64, 256;\nmov.b64 db, {b, 0x40000040};\n"
        "wgmma.mma_async.sync.aligned.m64n64k16.f32.bf16.bf16 {%0, %1, %2, %3, %4, %5, %6, %7, %8, %9, %10, %11, %12, "
        "%13, %14, %15, %16, %17, %18, %19, %20, %21, %22, %23, %24, %25, %26, %27, %28, %29, %30, %31}, {%40, %41, "
        "%42, %43}, db, 1, 1, 1, 1;\n"
        "add.u32 b, %64, 384;\nmov.b64 db, {b, 0x40000040};\n"
        "wgmma.mma_async.sync.aligned.m64n64k16.f32.bf16.bf16 {%0, %1, %2, %3, %4, %5, %6, %7, %8, %9, %10, %11, %12, "
        "%13, %14, %15, %16, %17, %18, %19, %20, %21, %22, %23, %24, %25, %26, %27, %28, %29, %30, %31}, {%44, %45, "
        "%46, %47}, db, 1, 1, 1, 1;\n"
        "add.u32 b, %64, 512;\nmov.b64 db, {b, 0x40000040};\n"
        "wgmma.mma_async.sync.aligned.m64n64k16.f32.bf16.bf16 {%0, %1, %2, %3, %4, %5, %6, %7, %8, %9, %10, %11, %12, "
        "%13, %14, %15, %16, %17, %18, %19, %20, %21, %22, %23, %24, %25, %26, %27, %28, %29, %30, %31}, {%48, %49, "
        "%50, %51}, db, 1, 1, 1, 1;\n"
        "add.u32 b, %64, 640;\nmov.b64 db, {b, 0x40000040};\n"
        "wgmma.mma_async.sync.aligned.m64n64k16.f32.bf16.bf16 {%0, %1, %2, %3, %4, %5, %6, %7, %8, %9, %10, %11, %12, "
        "%13, %14, %15, %16, %17, %18, %19, %20, %21, %22, %23, %24, %25, %26, %27, %28, %29, %30, %31}, {%52, %53, "
        "%54, %55}, db, 1, 1, 1, 1;\n"
        "add.u32 b, %64, 768;\nmov.b64 db, {b, 0x40000040};\n"
        "wgmma.mma_async.sync.aligned.m64n64k16.f32.bf16.bf16 {%0, %1, %2, %3, %4, %5, %6, %7, %8, %9, %10, %11, %12, "
        "%13, %14, %15, %16, %17, %18, %19, %20, %21, %22, %23, %24, %25, %26, %27, %28, %29, %30, %31}, {%56, %57, "
        "%58, %59}, db, 1, 1, 1, 1;\n"
        "add.u32 b, %64, 896;\nmov.b64 db, {b, 0x40000040};\n"
        "wgmma.mma_async.sync.aligned.m64n64k16.f32.bf16.bf16 {%0, %1, %2, %3, %4, %5, %6, %7, %8, %9, %10, %11, %12, "
        "%13, %14, %15, %16, %17, %18, %19, %20, %21, %22, %23, %24, %25, %26, %27, %28, %29, %30, %31}, {%60, %61, "
        "%62, %63}, db, 1, 1, 1, 1;\n"
        "wgmma.commit_group.sync.aligned;\n}"
        : "+f"(d[0]), "+f"(d[1]), "+f"(d[2]), "+f"(d[3]), "+f"(d[4]), "+f"(d[5]), "+f"(d[6]), "+f"(d[7]),
          "+f"(d[8]), "+f"(d[9]), "+f"(d[10]), "+f"(d[11]), "+f"(d[12]), "+f"(d[13]), "+f"(d[14]), "+f"(d[15]),
          "+f"(d[16]), "+f"(d[17]), "+f"(d[18]), "+f"(d[19]), "+f"(d[20]), "+f"(d[21]), "+f"(d[22]), "+f"(d[23]),
          "+f"(d[24]), "+f"(d[25]), "+f"(d[26]), "+f"(d[27]), "+f"(d[28]), "+f"(d[29]), "+f"(d[30]), "+f"(d[31])
        : "r"(a[0]), "r"(a[1]), "r"(a[2]), "r"(a[3]), "r"(a[4]), "r"(a[5]), "r"(a[6]), "r"(a[7]),
          "r"(a[8]), "r"(a[9]), "r"(a[10]), "r"(a[11]), "r"(a[12]), "r"(a[13]), "r"(a[14]), "r"(a[15]),
          "r"(a[16]), "r"(a[17]), "r"(a[18]), "r"(a[19]), "r"(a[20]), "r"(a[21]), "r"(a[22]), "r"(a[23]),
          "r"(a[24]), "r"(a[25]), "r"(a[26]), "r"(a[27]), "r"(a[28]), "r"(a[29]), "r"(a[30]), "r"(a[31]), "r"(b_lo) : "memory");
}
#define NRES 3
#define REV 1

struct Ring {
    uint32_t slot, phase;
    __device__ __forceinline__ void next() { if (++slot == NSLOT) { slot = 0; phase ^= 1; } }
};

__device__ __forceinline__ void token_wait(int wg) {
    asm volatile("bar.sync %0, 256;" :: "r"(wg + 1) : "memory");
}
__device__ __forceinline__ void token_pass(int wg) {
    asm volatile("bar.arrive %0, 256;" :: "r"(wg == 2 ? 1 : wg + 2) : "memory");
}

__global__ void __cluster_dims__(2, 1, 1) __launch_bounds__(512, 1)
mha_kernel(const __grid_constant__ Params p) {
    extern __shared__ __align__(1024) uint8_t smem_raw[];
    const uint32_t sb = smem_u32(smem_raw);
    const uint32_t bar_full = sb + OFF_BAR, bar_empty = bar_full + 8 * NSLOT, bar_q = bar_empty + 8 * NSLOT;
    const uint32_t rank = blockIdx.x & 1, cid = blockIdx.x >> 1, ncl = gridDim.x >> 1;
    const int warp = __shfl_sync(0xffffffff, threadIdx.x >> 5, 0);
    const int wg = warp >> 2;

    if (threadIdx.x == 0) {
        for (int i = 0; i < NSLOT; i++) { mbar_init(bar_full + 8 * i, 1); mbar_init(bar_empty + 8 * i, 6); }
        for (int i = 0; i < 3; i++) mbar_init(bar_q + 8 * i, 1);
        asm volatile("fence.mbarrier_init.release.cluster;" ::: "memory");
    }
    __syncthreads();
    asm volatile("barrier.cluster.arrive.relaxed.aligned;\nbarrier.cluster.wait.aligned;" ::: "memory");

    if (wg == 3) {
        asm volatile("setmaxnreg.dec.sync.aligned.u32 32;");
        if (threadIdx.x == 384) {
            uint32_t slot = 0, phase = 1;
            {
                const int r0 = (cid & p.hotmask) * S + rank * 192;
                for (int w = 0; w < 3; w++) {
                    mbar_expect_tx(bar_q + 8 * w, 32768);
                    for (int c = 0; c < 4; c++)
                        tma_load(sb + OFF_Q + (w * 4 + c) * 8192, &p.q, bar_q + 8 * w, c * 64, r0 + w * 64);
                }
            }
            for (int u = cid; u < NH; u += ncl) {
                const int kv0 = (u & p.hotmask) * S + rank * 64;
                const bool has_next = u + (int)ncl < NH;
                const int qn0 = ((u + ncl) & p.hotmask) * S + rank * 192;
#pragma unroll 1
                for (int s = 0; s < 24; s++) {
                    mbar_wait(bar_empty + 8 * slot, phase);
                    const uint32_t fb = bar_full + 8 * slot;
                    const uint32_t dst = sb + OFF_RING + slot * SLOT_BYTES + rank * 8192;
                    mbar_expect_tx(fb, SLOT_BYTES);
                    if (s < 12) tma_load_mc(dst, &p.k, fb, (s & 3) * 64, kv0 + (s >> 2) * 128);
                    else {
                        const int t = s - 12, c = t / 3, j = t - c * 3;
                        tma_load_mc(dst, &p.v, fb, c * 64, kv0 + (j == 0 ? 256 : j * 128 - 128));
                    }
                    if (s >= 18 && has_next) {
                        const int t = s - 18, w = t >> 1, c = (t & 1) * 2;
                        if (c == 0) mbar_expect_tx(bar_q + 8 * w, 32768);
                        tma_load(sb + OFF_Q + (w * 4 + c) * 8192, &p.q, bar_q + 8 * w, c * 64, qn0 + w * 64);
                        tma_load(sb + OFF_Q + (w * 4 + c + 1) * 8192, &p.q, bar_q + 8 * w, c * 64 + 64, qn0 + w * 64);
                    }
                    if (++slot == NSLOT) { slot = 0; phase ^= 1; }
                }
            }
            for (int i = 0; i < NSLOT; i++) {
                mbar_wait(bar_empty + 8 * slot, phase);
                if (++slot == NSLOT) { slot = 0; phase ^= 1; }
            }
        }
    } else {
        asm volatile("setmaxnreg.inc.sync.aligned.u32 160;");
        const int lane = threadIdx.x & 31, w4 = warp & 3;
        const bool rel = lane == 0 && w4 < 2;
        uint32_t rel_bar;
        asm("mapa.shared::cluster.u32 %0, %1, %2;" : "=r"(rel_bar) : "r"(bar_empty), "r"(w4 & 1));
        const uint32_t desc_q = desc_lo(sb + OFF_Q) + wg * 2048;
        const uint32_t desc_ring = desc_lo(sb + OFF_RING);
        Ring ring{0, 0};
        uint32_t qphase = 0;
        if (wg == 2) token_pass(2);

        for (int u = cid; u < NH; u += ncl) {
            uint32_t P[96];
            float ms[3][2], l0, l1;
            mbar_wait(bar_q + 8 * wg, qphase);
            qphase ^= 1;
#pragma unroll
            for (int j = 0; j < 3; j++) {
                float s[64];
                token_wait(wg);
                uint32_t prev = 0;
#pragma unroll
                for (int c = 0; c < 4; c++) {
                    mbar_wait(bar_full + 8 * ring.slot, ring.phase);
                    const uint32_t da = desc_q + c * 512, db = desc_ring + ring.slot * (SLOT_BYTES / 16);
                    if (c == 0) qk_group_init(s, da, db); else qk_group_acc(s, da, db);
                    if (c == 3) token_pass(wg);
                    if (c > 0) { wg_wait<1>(); mbar_arrive_cluster(rel_bar + 8 * prev, rel); }
                    prev = ring.slot;
                    ring.next();
                }
                wg_wait<0>();
                fence_regs(s);
                mbar_arrive_cluster(rel_bar + 8 * prev, rel);

                float m0 = fmaxf(s[0], s[1]), m1 = fmaxf(s[2], s[3]);
#pragma unroll
                for (int i = 1; i < 16; i++) {
                    m0 = fmaxf(m0, fmaxf(s[4 * i], s[4 * i + 1]));
                    m1 = fmaxf(m1, fmaxf(s[4 * i + 2], s[4 * i + 3]));
                }
                m0 = fmaxf(m0, __shfl_xor_sync(0xffffffff, m0, 1));
                m1 = fmaxf(m1, __shfl_xor_sync(0xffffffff, m1, 1));
                m0 = fmaxf(m0, __shfl_xor_sync(0xffffffff, m0, 2));
                m1 = fmaxf(m1, __shfl_xor_sync(0xffffffff, m1, 2));
                m0 *= SCALE_LOG2E; m1 *= SCALE_LOG2E;
                if (j > 0) { m0 = fmaxf(m0, ms[j - 1][0]); m1 = fmaxf(m1, ms[j - 1][1]); }
                ms[j][0] = m0; ms[j][1] = m1;
                float a0 = 0.f, a1 = 0.f;
#pragma unroll
                for (int ii = 0; ii < 16; ii++) {
                    const int i = (REV == 1 || (REV == 2 && j == 2)) ? 15 - ii : ii;
                    exp4(s[4 * i], s[4 * i + 1], s[4 * i + 2], s[4 * i + 3], m0, m1, P[32 * j + 2 * i], P[32 * j + 2 * i + 1], a0, a1);
                }
                if (j == 0) { l0 = a0; l1 = a1; }
                else if (j == 1) {
                    l0 = l0 * ex2(ms[0][0] - m0) + a0; l1 = l1 * ex2(ms[0][1] - m1) + a1;
                } else {
                    l0 = l0 * ex2(ms[1][0] - m0) + a0; l1 = l1 * ex2(ms[1][1] - m1) + a1;
                }
            }
            uint32_t dep = 0;
#pragma unroll
            for (int i = 64; i < 96; i++) dep |= P[i];
            dep &= 0x80008000u;
#pragma unroll
            for (int j = 0; j < NRES; j++) {
                const float f0 = ex2(ms[j][0] - ms[2][0]), f1 = ex2(ms[j][1] - ms[2][1]);
                const uint32_t g0 = pack_bf16(f0, f0) | dep, g1 = pack_bf16(f1, f1) | dep;
#pragma unroll
                for (int i = 0; i < 16; i++) {
                    scale_bf16x2(P[32 * j + 2 * i], g0);
                    scale_bf16x2(P[32 * j + 2 * i + 1], g1);
                }
            }
            l0 += __shfl_xor_sync(0xffffffff, l0, 1); l1 += __shfl_xor_sync(0xffffffff, l1, 1);
            l0 += __shfl_xor_sync(0xffffffff, l0, 2); l1 += __shfl_xor_sync(0xffffffff, l1, 2);
            const float inv0 = 1.0f / l0, inv1 = 1.0f / l1;
            uint32_t tid; asm volatile("mov.u32 %0, %%tid.x;" : "=r"(tid));
            const uint32_t ln = tid & 31, stage = sb + OFF_STAGE + (tid >> 5) * 1024;
            const uint32_t st_addr = stage + (ln & 7) * 128 + (((ln >> 3) ^ (ln & 7)) << 4);
            const uint32_t ld_addr = stage + (ln >> 3) * 128 + (((ln & 7) ^ (ln >> 3)) << 4);
            __nv_bfloat16* optr = p.o + ((size_t)((u & p.hotmask) * S + rank * 192 + (tid >> 5) * 16 + (ln >> 3))) * D + (ln & 7) * 8;

#pragma unroll 1
            for (int c = 0; c < 4; c++) {
                float o[32];
                token_wait(wg);
                uint32_t prev = 0;
#pragma unroll
                for (int j = 0; j < 3; j++) {
                    mbar_wait(bar_full + 8 * ring.slot, ring.phase);
                    const uint32_t db = desc_ring + ring.slot * (SLOT_BYTES / 16);
                    if (j == 0) pv_group_init(o, P + 64, db); else pv_group_acc(o, P + 32 * (j - 1), db);
                    if (j == 2) token_pass(wg);
                    if (j > 0) { wg_wait<1>(); mbar_arrive_cluster(rel_bar + 8 * prev, rel); }
                    prev = ring.slot;
                    ring.next();
                }
                wg_wait<0>();
                fence_regs(o);
                mbar_arrive_cluster(rel_bar + 8 * prev, rel);
#pragma unroll
                for (int h = 0; h < 2; h++) {
                    const float inv = h ? inv1 : inv0;
                    uint32_t r[8];
#pragma unroll
                    for (int i = 0; i < 8; i++) r[i] = pack_bf16(o[4 * i + 2 * h] * inv, o[4 * i + 2 * h + 1] * inv);
                    __syncwarp();
                    asm volatile("stmatrix.sync.aligned.m8n8.x4.shared.b16 [%0], {%1, %2, %3, %4};"
                                 :: "r"(st_addr), "r"(r[0]), "r"(r[1]), "r"(r[2]), "r"(r[3]) : "memory");
                    asm volatile("stmatrix.sync.aligned.m8n8.x4.shared.b16 [%0], {%1, %2, %3, %4};"
                                 :: "r"(st_addr ^ 64), "r"(r[4]), "r"(r[5]), "r"(r[6]), "r"(r[7]) : "memory");
                    __syncwarp();
                    uint4 x, y;
                    asm volatile("ld.shared.v4.b32 {%0, %1, %2, %3}, [%4];" : "=r"(x.x), "=r"(x.y), "=r"(x.z), "=r"(x.w) : "r"(ld_addr) : "memory");
                    asm volatile("ld.shared.v4.b32 {%0, %1, %2, %3}, [%4];" : "=r"(y.x), "=r"(y.y), "=r"(y.z), "=r"(y.w) : "r"((ld_addr + 512) ^ 64) : "memory");
                    *reinterpret_cast<uint4*>(optr + (h * 8) * D + c * 64) = x;
                    *reinterpret_cast<uint4*>(optr + (h * 8 + 4) * D + c * 64) = y;
                }
            }
        }
        if (wg == 0) token_wait(0);
    }
}

typedef CUresult (*EncodeFn)(CUtensorMap*, CUtensorMapDataType, cuuint32_t, void*, const cuuint64_t*, const cuuint64_t*,
                             const cuuint32_t*, const cuuint32_t*, CUtensorMapInterleave, CUtensorMapSwizzle,
                             CUtensorMapL2promotion, CUtensorMapFloatOOBfill);

void make_map(EncodeFn enc, CUtensorMap* m, const void* ptr) {
    cuuint64_t gdim[2] = {(cuuint64_t)D, (cuuint64_t)NH * S};
    cuuint64_t gstr[1] = {(cuuint64_t)D * 2};
    cuuint32_t box[2] = {64, 64};
    cuuint32_t estr[2] = {1, 1};
    enc(m, CU_TENSOR_MAP_DATA_TYPE_BFLOAT16, 2, const_cast<void*>(ptr), gdim, gstr, box, estr,
        CU_TENSOR_MAP_INTERLEAVE_NONE, CU_TENSOR_MAP_SWIZZLE_128B, CU_TENSOR_MAP_L2_PROMOTION_NONE,
        CU_TENSOR_MAP_FLOAT_OOB_FILL_NONE);
}

}

#define KSTREAM 0
#define HOTMASK 511

extern "C" void kernel_launch(void* const* d_in, const int* in_sizes, int n_in, void* d_out, int out_size) {
    static EncodeFn enc = nullptr;
    static int grid = 0;
    if (!enc) {
        void* fn = nullptr;
        cudaDriverEntryPointQueryResult qr;
        cudaGetDriverEntryPoint("cuTensorMapEncodeTiled", &fn, cudaEnableDefault, &qr);
        enc = (EncodeFn)fn;
        cudaFuncSetAttribute(mha_kernel, cudaFuncAttributeMaxDynamicSharedMemorySize, SMEM_BYTES);
        int dev = 0, sms = 0;
        cudaGetDevice(&dev);
        cudaDeviceGetAttribute(&sms, cudaDevAttrMultiProcessorCount, dev);
        grid = sms & ~1;
    }
    Params p;
    make_map(enc, &p.q, d_in[0]);
    make_map(enc, &p.k, d_in[1]);
    make_map(enc, &p.v, d_in[2]);
    p.o = (__nv_bfloat16*)d_out;
    p.hotmask = HOTMASK;
    mha_kernel<<<grid, 512, SMEM_BYTES, KSTREAM>>>(p);
}
```

```cpp
#include <cuda_runtime.h>
#include <cuda_bf16.h>
#include <cuda.h>
#include <stdint.h>

namespace {

constexpr int NH = 512;
constexpr int S = 384;
constexpr int D = 256;
constexpr int NSLOT = 8;
constexpr uint32_t SLOT_BYTES = 16384;
constexpr uint32_t OFF_Q = 0;
constexpr uint32_t OFF_RING = 98304;
constexpr uint32_t OFF_ONES = OFF_RING + NSLOT * SLOT_BYTES;
constexpr uint32_t OFF_BAR = OFF_ONES + 2048;
constexpr uint32_t SMEM_BYTES = OFF_BAR + 256;
constexpr float SCALE_LOG2E = 0.0625f * 1.4426950408889634f;
constexpr float LAZY_T = 8.0f;
constexpr int MAX_CL = 72, MAX_ITEMS = 640;

struct Params {
    CUtensorMap q, k, v;
    __nv_bfloat16* o;
    int n_items;
    int ef_from;
    int late_from;
    uint32_t start[MAX_CL];
    uint16_t item[MAX_ITEMS];
};
__device__ unsigned int g_drawn;
__device__ unsigned int g_ready;

__device__ __forceinline__ int item_head(uint32_t it) { return it & 511; }
__device__ __forceinline__ int item_nact(uint32_t it) { return (it >> 9) & 3; }
__device__ __forceinline__ int item_row0(uint32_t it, int rank) {
    return item_head(it) * S + ((it >> 11) & 3) * 128 + rank * 64 * item_nact(it);
}

__device__ __forceinline__ uint32_t smem_u32(const void* p) { return (uint32_t)__cvta_generic_to_shared(p); }
__device__ __forceinline__ uint32_t lds_u32(uint32_t addr) {
    uint32_t v; asm volatile("ld.shared.u32 %0, [%1];" : "=r"(v) : "r"(addr) : "memory"); return v;
}
__device__ __forceinline__ uint32_t map_to_cta(uint32_t addr, uint32_t cta) {
    uint32_t r; asm("mapa.shared::cluster.u32 %0, %1, %2;" : "=r"(r) : "r"(addr), "r"(cta)); return r;
}
__device__ __forceinline__ bool elect_one() {
    uint32_t ok;
    asm volatile("{\n.reg .pred p;\nelect.sync _|p, 0xffffffff;\nselp.u32 %0, 1, 0, p;\n}" : "=r"(ok));
    return ok;
}
__device__ __forceinline__ void mbar_init(uint32_t bar, uint32_t cnt) {
    asm volatile("mbarrier.init.shared::cta.b64 [%0], %1;" :: "r"(bar), "r"(cnt) : "memory");
}
__device__ __forceinline__ void mbar_init_fence() { asm volatile("fence.mbarrier_init.release.cluster;" ::: "memory"); }
__device__ __forceinline__ void mbar_arrive(uint32_t bar) {
    asm volatile("mbarrier.arrive.shared::cta.b64 _, [%0];" :: "r"(bar) : "memory");
}
__device__ __forceinline__ void mbar_expect_tx(uint32_t bar, uint32_t bytes) {
    asm volatile("mbarrier.arrive.expect_tx.shared::cta.b64 _, [%0], %1;" :: "r"(bar), "r"(bytes) : "memory");
}
__device__ __forceinline__ void mbar_arrive_cluster(uint32_t bar, bool pred) {
    asm volatile("{\n.reg .pred p;\nsetp.ne.b32 p, %1, 0;\n@p mbarrier.arrive.shared::cluster.b64 _, [%0];\n}"
                 :: "r"(bar), "r"((int)pred) : "memory");
}
__device__ __forceinline__ void mbar_wait(uint32_t bar, uint32_t parity) {
    asm volatile("{\n.reg .pred p;\n.reg .b32 n;\n"
                 "mbarrier.try_wait.parity.shared::cta.b64 p, [%0], %1;\n"
                 "@p bra DONE_%=;\n"
                 "mov.b32 n, 0;\n"
                 "WAIT_%=:\n"
                 "mbarrier.try_wait.parity.shared::cta.b64 p, [%0], %1;\n"
                 "@p bra DONE_%=;\n"
                 "add.u32 n, n, 1;\n"
                 "setp.lt.u32 p, n, 0x400000;\n"
                 "@p bra WAIT_%=;\n"
                 "trap;\n"
                 "DONE_%=:\n}"
                 :: "r"(bar), "r"(parity) : "memory");
}
__device__ __forceinline__ void mbar_spin(uint32_t bar, uint32_t parity) {
    asm volatile("{\n.reg .pred p;\n"
                 "WAIT_%=:\n"
                 "mbarrier.try_wait.parity.shared::cta.b64 p, [%0], %1;\n"
                 "@!p bra WAIT_%=;\n}"
                 :: "r"(bar), "r"(parity) : "memory");
}
__device__ __forceinline__ void tma_load(uint32_t dst, const CUtensorMap* m, uint32_t bar, int c0, int c1, uint64_t pol) {
    asm volatile("cp.async.bulk.tensor.2d.shared::cluster.global.mbarrier::complete_tx::bytes.L2::cache_hint"
                 " [%0], [%1, {%3, %4}], [%2], %5;"
                 :: "r"(dst), "l"(m), "r"(bar), "r"(c0), "r"(c1), "l"(pol) : "memory");
}
__device__ __forceinline__ void tma_load_mc(uint32_t dst, const CUtensorMap* m, uint32_t bar, int c0, int c1, uint64_t pol) {
    asm volatile("cp.async.bulk.tensor.2d.shared::cluster.global.mbarrier::complete_tx::bytes.multicast::cluster.L2::cache_hint"
                 " [%0], [%1, {%3, %4}], [%2], %5, %6;"
                 :: "r"(dst), "l"(m), "r"(bar), "r"(c0), "r"(c1), "h"((uint16_t)3), "l"(pol) : "memory");
}
__device__ __forceinline__ uint64_t policy_normal() {
    uint64_t p; asm("createpolicy.fractional.L2::evict_normal.b64 %0, 1.0;" : "=l"(p)); return p;
}
__device__ __forceinline__ uint64_t policy_first() {
    uint64_t p; asm("createpolicy.fractional.L2::evict_first.b64 %0, 1.0;" : "=l"(p)); return p;
}
template <int N> __device__ __forceinline__ void wg_wait() { asm volatile("wgmma.wait_group.sync.aligned %0;" :: "n"(N) : "memory"); }
template <int N> __device__ __forceinline__ void fence_regs(float (&d)[N]) {
#pragma unroll
    for (int i = 0; i < N; i++) asm volatile("" : "+f"(d[i]) :: "memory");
}
__device__ __forceinline__ float ex2(float x) { float y; asm("ex2.approx.ftz.f32 %0, %1;" : "=f"(y) : "f"(x)); return y; }
__device__ __forceinline__ float rcp(float x) { float y; asm("rcp.approx.ftz.f32 %0, %1;" : "=f"(y) : "f"(x)); return y; }
__device__ __forceinline__ uint32_t pack_bf16(float lo, float hi) {
    uint32_t r; asm("cvt.rn.bf16x2.f32 %0, %1, %2;" : "=r"(r) : "f"(hi), "f"(lo)); return r;
}
__device__ __forceinline__ uint32_t mul_bf16x2(uint32_t a, uint32_t b) {
    uint32_t r; asm("mul.rn.bf16x2 %0, %1, %2;" : "=r"(r) : "r"(a), "r"(b)); return r;
}
__device__ __forceinline__ uint32_t exp_pack(float s0, float s1, float m) {
    return pack_bf16(ex2(fmaf(s0, SCALE_LOG2E, -m)), ex2(fmaf(s1, SCALE_LOG2E, -m)));
}
__device__ __forceinline__ void quad_swap(uint32_t& x, uint32_t& y, bool hi, int mask) {
    const uint32_t r = __shfl_xor_sync(0xffffffff, hi ? x : y, mask);
    if (hi) x = r; else y = r;
}
__device__ __forceinline__ uint32_t desc_lo(uint32_t addr) { return ((addr >> 4) & 0x3FFF) | (1u << 16); }

__device__ __forceinline__ void qk_group_init(float (&d)[64], uint32_t a_lo, uint32_t b_lo) {
    asm volatile("{\n.reg .b64 da, db;\n.reg .b32 a, b;\n"
        "wgmma.fence.sync.aligned;\n"
        "add.u32 a, %64, 0;\nadd.u32 b, %65, 0;\nmov.b64 da, {a, 0x40000040};\nmov.b64 db, {b, 0x40000040};\n"
        "wgmma.mma_async.sync.aligned.m64n128k16.f32.bf16.bf16 {%0, %1, %2, %3, %4, %5, %6, %7, %8, %9, %10, %11, %12, "
        "%13, %14, %15, %16, %17, %18, %19, %20, %21, %22, %23, %24, %25, %26, %27, %28, %29, %30, %31, %32, %33, %34, "
        "%35, %36, %37, %38, %39, %40, %41, %42, %43, %44, %45, %46, %47, %48, %49, %50, %51, %52, %53, %54, %55, %56, "
        "%57, %58, %59, %60, %61, %62, %63}, da, db, 0, 1, 1, 0, 0;\n"
        "add.u32 a, %64, 2;\nadd.u32 b, %65, 2;\nmov.b64 da, {a, 0x40000040};\nmov.b64 db, {b, 0x40000040};\n"
        "wgmma.mma_async.sync.aligned.m64n128k16.f32.bf16.bf16 {%0, %1, %2, %3, %4, %5, %6, %7, %8, %9, %10, %11, %12, "
        "%13, %14, %15, %16, %17, %18, %19, %20, %21, %22, %23, %24, %25, %26, %27, %28, %29, %30, %31, %32, %33, %34, "
        "%35, %36, %37, %38, %39, %40, %41, %42, %43, %44, %45, %46, %47, %48, %49, %50, %51, %52, %53, %54, %55, %56, "
        "%57, %58, %59, %60, %61, %62, %63}, da, db, 1, 1, 1, 0, 0;\n"
        "add.u32 a, %64, 4;\nadd.u32 b, %65, 4;\nmov.b64 da, {a, 0x40000040};\nmov.b64 db, {b, 0x40000040};\n"
        "wgmma.mma_async.sync.aligned.m64n128k16.f32.bf16.bf16 {%0, %1, %2, %3, %4, %5, %6, %7, %8, %9, %10, %11, %12, "
        "%13, %14, %15, %16, %17, %18, %19, %20, %21, %22, %23, %24, %25, %26, %27, %28, %29, %30, %31, %32, %33, %34, "
        "%35, %36, %37, %38, %39, %40, %41, %42, %43, %44, %45, %46, %47, %48, %49, %50, %51, %52, %53, %54, %55, %56, "
        "%57, %58, %59, %60, %61, %62, %63}, da, db, 1, 1, 1, 0, 0;\n"
        "add.u32 a, %64, 6;\nadd.u32 b, %65, 6;\nmov.b64 da, {a, 0x40000040};\nmov.b64 db, {b, 0x40000040};\n"
        "wgmma.mma_async.sync.aligned.m64n128k16.f32.bf16.bf16 {%0, %1, %2, %3, %4, %5, %6, %7, %8, %9, %10, %11, %12, "
        "%13, %14, %15, %16, %17, %18, %19, %20, %21, %22, %23, %24, %25, %26, %27, %28, %29, %30, %31, %32, %33, %34, "
        "%35, %36, %37, %38, %39, %40, %41, %42, %43, %44, %45, %46, %47, %48, %49, %50, %51, %52, %53, %54, %55, %56, "
        "%57, %58, %59, %60, %61, %62, %63}, da, db, 1, 1, 1, 0, 0;\n"
        "wgmma.commit_group.sync.aligned;\n}"
        : "=f"(d[0]), "=f"(d[1]), "=f"(d[2]), "=f"(d[3]), "=f"(d[4]), "=f"(d[5]), "=f"(d[6]), "=f"(d[7]),
          "=f"(d[8]), "=f"(d[9]), "=f"(d[10]), "=f"(d[11]), "=f"(d[12]), "=f"(d[13]), "=f"(d[14]), "=f"(d[15]),
          "=f"(d[16]), "=f"(d[17]), "=f"(d[18]), "=f"(d[19]), "=f"(d[20]), "=f"(d[21]), "=f"(d[22]), "=f"(d[23]),
          "=f"(d[24]), "=f"(d[25]), "=f"(d[26]), "=f"(d[27]), "=f"(d[28]), "=f"(d[29]), "=f"(d[30]), "=f"(d[31]),
          "=f"(d[32]), "=f"(d[33]), "=f"(d[34]), "=f"(d[35]), "=f"(d[36]), "=f"(d[37]), "=f"(d[38]), "=f"(d[39]),
          "=f"(d[40]), "=f"(d[41]), "=f"(d[42]), "=f"(d[43]), "=f"(d[44]), "=f"(d[45]), "=f"(d[46]), "=f"(d[47]),
          "=f"(d[48]), "=f"(d[49]), "=f"(d[50]), "=f"(d[51]), "=f"(d[52]), "=f"(d[53]), "=f"(d[54]), "=f"(d[55]),
          "=f"(d[56]), "=f"(d[57]), "=f"(d[58]), "=f"(d[59]), "=f"(d[60]), "=f"(d[61]), "=f"(d[62]), "=f"(d[63])
        : "r"(a_lo), "r"(b_lo) : "memory");
}
__device__ __forceinline__ void qk_group_acc(float (&d)[64], uint32_t a_lo, uint32_t b_lo) {
    asm volatile("{\n.reg .b64 da, db;\n.reg .b32 a, b;\n"
        "wgmma.fence.sync.aligned;\n"
        "add.u32 a, %64, 0;\nadd.u32 b, %65, 0;\nmov.b64 da, {a, 0x40000040};\nmov.b64 db, {b, 0x40000040};\n"
        "wgmma.mma_async.sync.aligned.m64n128k16.f32.bf16.bf16 {%0, %1, %2, %3, %4, %5, %6, %7, %8, %9, %10, %11, %12, "
        "%13, %14, %15, %16, %17, %18, %19, %20, %21, %22, %23, %24, %25, %26, %27, %28, %29, %30, %31, %32, %33, %34, "
        "%35, %36, %37, %38, %39, %40, %41, %42, %43, %44, %45, %46, %47, %48, %49, %50, %51, %52, %53, %54, %55, %56, "
        "%57, %58, %59, %60, %61, %62, %63}, da, db, 1, 1, 1, 0, 0;\n"
        "add.u32 a, %64, 2;\nadd.u32 b, %65, 2;\nmov.b64 da, {a, 0x40000040};\nmov.b64 db, {b, 0x40000040};\n"
        "wgmma.mma_async.sync.aligned.m64n128k16.f32.bf16.bf16 {%0, %1, %2, %3, %4, %5, %6, %7, %8, %9, %10, %11, %12, "
        "%13, %14, %15, %16, %17, %18, %19, %20, %21, %22, %23, %24, %25, %26, %27, %28, %29, %30, %31, %32, %33, %34, "
        "%35, %36, %37, %38, %39, %40, %41, %42, %43, %44, %45, %46, %47, %48, %49, %50, %51, %52, %53, %54, %55, %56, "
        "%57, %58, %59, %60, %61, %62, %63}, da, db, 1, 1, 1, 0, 0;\n"
        "add.u32 a, %64, 4;\nadd.u32 b, %65, 4;\nmov.b64 da, {a, 0x40000040};\nmov.b64 db, {b, 0x40000040};\n"
        "wgmma.mma_async.sync.aligned.m64n128k16.f32.bf16.bf16 {%0, %1, %2, %3, %4, %5, %6, %7, %8, %9, %10, %11, %12, "
        "%13, %14, %15, %16, %17, %18, %19, %20, %21, %22, %23, %24, %25, %26, %27, %28, %29, %30, %31, %32, %33, %34, "
        "%35, %36, %37, %38, %39, %40, %41, %42, %43, %44, %45, %46, %47, %48, %49, %50, %51, %52, %53, %54, %55, %56, "
        "%57, %58, %59, %60, %61, %62, %63}, da, db, 1, 1, 1, 0, 0;\n"
        "add.u32 a, %64, 6;\nadd.u32 b, %65, 6;\nmov.b64 da, {a, 0x40000040};\nmov.b64 db, {b, 0x40000040};\n"
        "wgmma.mma_async.sync.aligned.m64n128k16.f32.bf16.bf16 {%0, %1, %2, %3, %4, %5, %6, %7, %8, %9, %10, %11, %12, "
        "%13, %14, %15, %16, %17, %18, %19, %20, %21, %22, %23, %24, %25, %26, %27, %28, %29, %30, %31, %32, %33, %34, "
        "%35, %36, %37, %38, %39, %40, %41, %42, %43, %44, %45, %46, %47, %48, %49, %50, %51, %52, %53, %54, %55, %56, "
        "%57, %58, %59, %60, %61, %62, %63}, da, db, 1, 1, 1, 0, 0;\n"
        "wgmma.commit_group.sync.aligned;\n}"
        : "+f"(d[0]), "+f"(d[1]), "+f"(d[2]), "+f"(d[3]), "+f"(d[4]), "+f"(d[5]), "+f"(d[6]), "+f"(d[7]),
          "+f"(d[8]), "+f"(d[9]), "+f"(d[10]), "+f"(d[11]), "+f"(d[12]), "+f"(d[13]), "+f"(d[14]), "+f"(d[15]),
          "+f"(d[16]), "+f"(d[17]), "+f"(d[18]), "+f"(d[19]), "+f"(d[20]), "+f"(d[21]), "+f"(d[22]), "+f"(d[23]),
          "+f"(d[24]), "+f"(d[25]), "+f"(d[26]), "+f"(d[27]), "+f"(d[28]), "+f"(d[29]), "+f"(d[30]), "+f"(d[31]),
          "+f"(d[32]), "+f"(d[33]), "+f"(d[34]), "+f"(d[35]), "+f"(d[36]), "+f"(d[37]), "+f"(d[38]), "+f"(d[39]),
          "+f"(d[40]), "+f"(d[41]), "+f"(d[42]), "+f"(d[43]), "+f"(d[44]), "+f"(d[45]), "+f"(d[46]), "+f"(d[47]),
          "+f"(d[48]), "+f"(d[49]), "+f"(d[50]), "+f"(d[51]), "+f"(d[52]), "+f"(d[53]), "+f"(d[54]), "+f"(d[55]),
          "+f"(d[56]), "+f"(d[57]), "+f"(d[58]), "+f"(d[59]), "+f"(d[60]), "+f"(d[61]), "+f"(d[62]), "+f"(d[63])
        : "r"(a_lo), "r"(b_lo) : "memory");
}
__device__ __forceinline__ void pv_group_init(float (&d)[32], const uint32_t* a, uint32_t b_lo) {
    asm volatile("{\n.reg .b64 db;\n.reg .b32 b;\n"
        "wgmma.fence.sync.aligned;\n"
        "add.u32 b, %64, 0;\nmov.b64 db, {b, 0x40000040};\n"
        "wgmma.mma_async.sync.aligned.m64n64k16.f32.bf16.bf16 {%0, %1, %2, %3, %4, %5, %6, %7, %8, %9, %10, %11, %12, "
        "%13, %14, %15, %16, %17, %18, %19, %20, %21, %22, %23, %24, %25, %26, %27, %28, %29, %30, %31}, {%32, %33, "
        "%34, %35}, db, 0, 1, 1, 1;\n"
        "add.u32 b, %64, 128;\nmov.b64 db, {b, 0x40000040};\n"
        "wgmma.mma_async.sync.aligned.m64n64k16.f32.bf16.bf16 {%0, %1, %2, %3, %4, %5, %6, %7, %8, %9, %10, %11, %12, "
        "%13, %14, %15, %16, %17, %18, %19, %20, %21, %22, %23, %24, %25, %26, %27, %28, %29, %30, %31}, {%36, %37, "
        "%38, %39}, db, 1, 1, 1, 1;\n"
        "add.u32 b, %64, 256;\nmov.b64 db, {b, 0x40000040};\n"
        "wgmma.mma_async.sync.aligned.m64n64k16.f32.bf16.bf16 {%0, %1, %2, %3, %4, %5, %6, %7, %8, %9, %10, %11, %12, "
        "%13, %14, %15, %16, %17, %18, %19, %20, %21, %22, %23, %24, %25, %26, %27, %28, %29, %30, %31}, {%40, %41, "
        "%42, %43}, db, 1, 1, 1, 1;\n"
        "add.u32 b, %64, 384;\nmov.b64 db, {b, 0x40000040};\n"
        "wgmma.mma_async.sync.aligned.m64n64k16.f32.bf16.bf16 {%0, %1, %2, %3, %4, %5, %6, %7, %8, %9, %10, %11, %12, "
        "%13, %14, %15, %16, %17, %18, %19, %20, %21, %22, %23, %24, %25, %26, %27, %28, %29, %30, %31}, {%44, %45, "
        "%46, %47}, db, 1, 1, 1, 1;\n"
        "add.u32 b, %64, 512;\nmov.b64 db, {b, 0x40000040};\n"
        "wgmma.mma_async.sync.aligned.m64n64k16.f32.bf16.bf16 {%0, %1, %2, %3, %4, %5, %6, %7, %8, %9, %10, %11, %12, "
        "%13, %14, %15, %16, %17, %18, %19, %20, %21, %22, %23, %24, %25, %26, %27, %28, %29, %30, %31}, {%48, %49, "
        "%50, %51}, db, 1, 1, 1, 1;\n"
        "add.u32 b, %64, 640;\nmov.b64 db, {b, 0x40000040};\n"
        "wgmma.mma_async.sync.aligned.m64n64k16.f32.bf16.bf16 {%0, %1, %2, %3, %4, %5, %6, %7, %8, %9, %10, %11, %12, "
        "%13, %14, %15, %16, %17, %18, %19, %20, %21, %22, %23, %24, %25, %26, %27, %28, %29, %30, %31}, {%52, %53, "
        "%54, %55}, db, 1, 1, 1, 1;\n"
        "add.u32 b, %64, 768;\nmov.b64 db, {b, 0x40000040};\n"
        "wgmma.mma_async.sync.aligned.m64n64k16.f32.bf16.bf16 {%0, %1, %2, %3, %4, %5, %6, %7, %8, %9, %10, %11, %12, "
        "%13, %14, %15, %16, %17, %18, %19, %20, %21, %22, %23, %24, %25, %26, %27, %28, %29, %30, %31}, {%56, %57, "
        "%58, %59}, db, 1, 1, 1, 1;\n"
        "add.u32 b, %64, 896;\nmov.b64 db, {b, 0x40000040};\n"
        "wgmma.mma_async.sync.aligned.m64n64k16.f32.bf16.bf16 {%0, %1, %2, %3, %4, %5, %6, %7, %8, %9, %10, %11, %12, "
        "%13, %14, %15, %16, %17, %18, %19, %20, %21, %22, %23, %24, %25, %26, %27, %28, %29, %30, %31}, {%60, %61, "
        "%62, %63}, db, 1, 1, 1, 1;\n"
        "wgmma.commit_group.sync.aligned;\n}"
        : "=f"(d[0]), "=f"(d[1]), "=f"(d[2]), "=f"(d[3]), "=f"(d[4]), "=f"(d[5]), "=f"(d[6]), "=f"(d[7]),
          "=f"(d[8]), "=f"(d[9]), "=f"(d[10]), "=f"(d[11]), "=f"(d[12]), "=f"(d[13]), "=f"(d[14]), "=f"(d[15]),
          "=f"(d[16]), "=f"(d[17]), "=f"(d[18]), "=f"(d[19]), "=f"(d[20]), "=f"(d[21]), "=f"(d[22]), "=f"(d[23]),
          "=f"(d[24]), "=f"(d[25]), "=f"(d[26]), "=f"(d[27]), "=f"(d[28]), "=f"(d[29]), "=f"(d[30]), "=f"(d[31])
        : "r"(a[0]), "r"(a[1]), "r"(a[2]), "r"(a[3]), "r"(a[4]), "r"(a[5]), "r"(a[6]), "r"(a[7]),
          "r"(a[8]), "r"(a[9]), "r"(a[10]), "r"(a[11]), "r"(a[12]), "r"(a[13]), "r"(a[14]), "r"(a[15]),
          "r"(a[16]), "r"(a[17]), "r"(a[18]), "r"(a[19]), "r"(a[20]), "r"(a[21]), "r"(a[22]), "r"(a[23]),
          "r"(a[24]), "r"(a[25]), "r"(a[26]), "r"(a[27]), "r"(a[28]), "r"(a[29]), "r"(a[30]), "r"(a[31]), "r"(b_lo) : "memory");
}
__device__ __forceinline__ void pv_group_acc(float (&d)[32], const uint32_t* a, uint32_t b_lo) {
    asm volatile("{\n.reg .b64 db;\n.reg .b32 b;\n"
        "wgmma.fence.sync.aligned;\n"
        "add.u32 b, %64, 0;\nmov.b64 db, {b, 0x40000040};\n"
        "wgmma.mma_async.sync.aligned.m64n64k16.f32.bf16.bf16 {%0, %1, %2, %3, %4, %5, %6, %7, %8, %9, %10, %11, %12, "
        "%13, %14, %15, %16, %17, %18, %19, %20, %21, %22, %23, %24, %25, %26, %27, %28, %29, %30, %31}, {%32, %33, "
        "%34, %35}, db, 1, 1, 1, 1;\n"
        "add.u32 b, %64, 128;\nmov.b64 db, {b, 0x40000040};\n"
        "wgmma.mma_async.sync.aligned.m64n64k16.f32.bf16.bf16 {%0, %1, %2, %3, %4, %5, %6, %7, %8, %9, %10, %11, %12, "
        "%13, %14, %15, %16, %17, %18, %19, %20, %21, %22, %23, %24, %25, %26, %27, %28, %29, %30, %31}, {%36, %37, "
        "%38, %39}, db, 1, 1, 1, 1;\n"
        "add.u32 b, %64, 256;\nmov.b64 db, {b, 0x40000040};\n"
        "wgmma.mma_async.sync.aligned.m64n64k16.f32.bf16.bf16 {%0, %1, %2, %3, %4, %5, %6, %7, %8, %9, %10, %11, %12, "
        "%13, %14, %15, %16, %17, %18, %19, %20, %21, %22, %23, %24, %25, %26, %27, %28, %29, %30, %31}, {%40, %41, "
        "%42, %43}, db, 1, 1, 1, 1;\n"
        "add.u32 b, %64, 384;\nmov.b64 db, {b, 0x40000040};\n"
        "wgmma.mma_async.sync.aligned.m64n64k16.f32.bf16.bf16 {%0, %1, %2, %3, %4, %5, %6, %7, %8, %9, %10, %11, %12, "
        "%13, %14, %15, %16, %17, %18, %19, %20, %21, %22, %23, %24, %25, %26, %27, %28, %29, %30, %31}, {%44, %45, "
        "%46, %47}, db, 1, 1, 1, 1;\n"
        "add.u32 b, %64, 512;\nmov.b64 db, {b, 0x40000040};\n"
        "wgmma.mma_async.sync.aligned.m64n64k16.f32.bf16.bf16 {%0, %1, %2, %3, %4, %5, %6, %7, %8, %9, %10, %11, %12, "
        "%13, %14, %15, %16, %17, %18, %19, %20, %21, %22, %23, %24, %25, %26, %27, %28, %29, %30, %31}, {%48, %49, "
        "%50, %51}, db, 1, 1, 1, 1;\n"
        "add.u32 b, %64, 640;\nmov.b64 db, {b, 0x40000040};\n"
        "wgmma.mma_async.sync.aligned.m64n64k16.f32.bf16.bf16 {%0, %1, %2, %3, %4, %5, %6, %7, %8, %9, %10, %11, %12, "
        "%13, %14, %15, %16, %17, %18, %19, %20, %21, %22, %23, %24, %25, %26, %27, %28, %29, %30, %31}, {%52, %53, "
        "%54, %55}, db, 1, 1, 1, 1;\n"
        "add.u32 b, %64, 768;\nmov.b64 db, {b, 0x40000040};\n"
        "wgmma.mma_async.sync.aligned.m64n64k16.f32.bf16.bf16 {%0, %1, %2, %3, %4, %5, %6, %7, %8, %9, %10, %11, %12, "
        "%13, %14, %15, %16, %17, %18, %19, %20, %21, %22, %23, %24, %25, %26, %27, %28, %29, %30, %31}, {%56, %57, "
        "%58, %59}, db, 1, 1, 1, 1;\n"
        "add.u32 b, %64, 896;\nmov.b64 db, {b, 0x40000040};\n"
        "wgmma.mma_async.sync.aligned.m64n64k16.f32.bf16.bf16 {%0, %1, %2, %3, %4, %5, %6, %7, %8, %9, %10, %11, %12, "
        "%13, %14, %15, %16, %17, %18, %19, %20, %21, %22, %23, %24, %25, %26, %27, %28, %29, %30, %31}, {%60, %61, "
        "%62, %63}, db, 1, 1, 1, 1;\n"
        "wgmma.commit_group.sync.aligned;\n}"
        : "+f"(d[0]), "+f"(d[1]), "+f"(d[2]), "+f"(d[3]), "+f"(d[4]), "+f"(d[5]), "+f"(d[6]), "+f"(d[7]),
          "+f"(d[8]), "+f"(d[9]), "+f"(d[10]), "+f"(d[11]), "+f"(d[12]), "+f"(d[13]), "+f"(d[14]), "+f"(d[15]),
          "+f"(d[16]), "+f"(d[17]), "+f"(d[18]), "+f"(d[19]), "+f"(d[20]), "+f"(d[21]), "+f"(d[22]), "+f"(d[23]),
          "+f"(d[24]), "+f"(d[25]), "+f"(d[26]), "+f"(d[27]), "+f"(d[28]), "+f"(d[29]), "+f"(d[30]), "+f"(d[31])
        : "r"(a[0]), "r"(a[1]), "r"(a[2]), "r"(a[3]), "r"(a[4]), "r"(a[5]), "r"(a[6]), "r"(a[7]),
          "r"(a[8]), "r"(a[9]), "r"(a[10]), "r"(a[11]), "r"(a[12]), "r"(a[13]), "r"(a[14]), "r"(a[15]),
          "r"(a[16]), "r"(a[17]), "r"(a[18]), "r"(a[19]), "r"(a[20]), "r"(a[21]), "r"(a[22]), "r"(a[23]),
          "r"(a[24]), "r"(a[25]), "r"(a[26]), "r"(a[27]), "r"(a[28]), "r"(a[29]), "r"(a[30]), "r"(a[31]), "r"(b_lo) : "memory");
}
__device__ __forceinline__ void pvsum_group_init(float (&d)[36], const uint32_t* a, uint32_t b_lo) {
    asm volatile("{\n.reg .b64 db;\n.reg .b32 b;\n"
        "wgmma.fence.sync.aligned;\n"
        "add.u32 b, %68, 0;\nmov.b64 db, {b, 0x40000040};\n"
        "wgmma.mma_async.sync.aligned.m64n72k16.f32.bf16.bf16 {%0, %1, %2, %3, %4, %5, %6, %7, %8, %9, %10, %11, %12, "
        "%13, %14, %15, %16, %17, %18, %19, %20, %21, %22, %23, %24, %25, %26, %27, %28, %29, %30, %31, %32, %33, %34, "
        "%35}, {%36, %37, %38, %39}, db, 0, 1, 1, 1;\n"
        "add.u32 b, %68, 4286578816;\nmov.b64 db, {b, 0x40000040};\n"
        "wgmma.mma_async.sync.aligned.m64n72k16.f32.bf16.bf16 {%0, %1, %2, %3, %4, %5, %6, %7, %8, %9, %10, %11, %12, "
        "%13, %14, %15, %16, %17, %18, %19, %20, %21, %22, %23, %24, %25, %26, %27, %28, %29, %30, %31, %32, %33, %34, "
        "%35}, {%40, %41, %42, %43}, db, 1, 1, 1, 1;\n"
        "add.u32 b, %68, 4278190336;\nmov.b64 db, {b, 0x40000040};\n"
        "wgmma.mma_async.sync.aligned.m64n72k16.f32.bf16.bf16 {%0, %1, %2, %3, %4, %5, %6, %7, %8, %9, %10, %11, %12, "
        "%13, %14, %15, %16, %17, %18, %19, %20, %21, %22, %23, %24, %25, %26, %27, %28, %29, %30, %31, %32, %33, %34, "
        "%35}, {%44, %45, %46, %47}, db, 1, 1, 1, 1;\n"
        "add.u32 b, %68, 4269801856;\nmov.b64 db, {b, 0x40000040};\n"
        "wgmma.mma_async.sync.aligned.m64n72k16.f32.bf16.bf16 {%0, %1, %2, %3, %4, %5, %6, %7, %8, %9, %10, %11, %12, "
        "%13, %14, %15, %16, %17, %18, %19, %20, %21, %22, %23, %24, %25, %26, %27, %28, %29, %30, %31, %32, %33, %34, "
        "%35}, {%48, %49, %50, %51}, db, 1, 1, 1, 1;\n"
        "add.u32 b, %68, 4261413376;\nmov.b64 db, {b, 0x40000040};\n"
        "wgmma.mma_async.sync.aligned.m64n72k16.f32.bf16.bf16 {%0, %1, %2, %3, %4, %5, %6, %7, %8, %9, %10, %11, %12, "
        "%13, %14, %15, %16, %17, %18, %19, %20, %21, %22, %23, %24, %25, %26, %27, %28, %29, %30, %31, %32, %33, %34, "
        "%35}, {%52, %53, %54, %55}, db, 1, 1, 1, 1;\n"
        "add.u32 b, %68, 4253024896;\nmov.b64 db, {b, 0x40000040};\n"
        "wgmma.mma_async.sync.aligned.m64n72k16.f32.bf16.bf16 {%0, %1, %2, %3, %4, %5, %6, %7, %8, %9, %10, %11, %12, "
        "%13, %14, %15, %16, %17, %18, %19, %20, %21, %22, %23, %24, %25, %26, %27, %28, %29, %30, %31, %32, %33, %34, "
        "%35}, {%56, %57, %58, %59}, db, 1, 1, 1, 1;\n"
        "add.u32 b, %68, 4244636416;\nmov.b64 db, {b, 0x40000040};\n"
        "wgmma.mma_async.sync.aligned.m64n72k16.f32.bf16.bf16 {%0, %1, %2, %3, %4, %5, %6, %7, %8, %9, %10, %11, %12, "
        "%13, %14, %15, %16, %17, %18, %19, %20, %21, %22, %23, %24, %25, %26, %27, %28, %29, %30, %31, %32, %33, %34, "
        "%35}, {%60, %61, %62, %63}, db, 1, 1, 1, 1;\n"
        "add.u32 b, %68, 4236247936;\nmov.b64 db, {b, 0x40000040};\n"
        "wgmma.mma_async.sync.aligned.m64n72k16.f32.bf16.bf16 {%0, %1, %2, %3, %4, %5, %6, %7, %8, %9, %10, %11, %12, "
        "%13, %14, %15, %16, %17, %18, %19, %20, %21, %22, %23, %24, %25, %26, %27, %28, %29, %30, %31, %32, %33, %34, "
        "%35}, {%64, %65, %66, %67}, db, 1, 1, 1, 1;\n"
        "wgmma.commit_group.sync.aligned;\n}"
        : "=f"(d[0]), "=f"(d[1]), "=f"(d[2]), "=f"(d[3]), "=f"(d[4]), "=f"(d[5]), "=f"(d[6]), "=f"(d[7]),
          "=f"(d[8]), "=f"(d[9]), "=f"(d[10]), "=f"(d[11]), "=f"(d[12]), "=f"(d[13]), "=f"(d[14]), "=f"(d[15]),
          "=f"(d[16]), "=f"(d[17]), "=f"(d[18]), "=f"(d[19]), "=f"(d[20]), "=f"(d[21]), "=f"(d[22]), "=f"(d[23]),
          "=f"(d[24]), "=f"(d[25]), "=f"(d[26]), "=f"(d[27]), "=f"(d[28]), "=f"(d[29]), "=f"(d[30]), "=f"(d[31]),
          "=f"(d[32]), "=f"(d[33]), "=f"(d[34]), "=f"(d[35])
        : "r"(a[0]), "r"(a[1]), "r"(a[2]), "r"(a[3]), "r"(a[4]), "r"(a[5]), "r"(a[6]), "r"(a[7]),
          "r"(a[8]), "r"(a[9]), "r"(a[10]), "r"(a[11]), "r"(a[12]), "r"(a[13]), "r"(a[14]), "r"(a[15]),
          "r"(a[16]), "r"(a[17]), "r"(a[18]), "r"(a[19]), "r"(a[20]), "r"(a[21]), "r"(a[22]), "r"(a[23]),
          "r"(a[24]), "r"(a[25]), "r"(a[26]), "r"(a[27]), "r"(a[28]), "r"(a[29]), "r"(a[30]), "r"(a[31]), "r"(b_lo) : "memory");
}
__device__ __forceinline__ void pvsum_group_acc(float (&d)[36], const uint32_t* a, uint32_t b_lo) {
    asm volatile("{\n.reg .b64 db;\n.reg .b32 b;\n"
        "wgmma.fence.sync.aligned;\n"
        "add.u32 b, %68, 0;\nmov.b64 db, {b, 0x40000040};\n"
        "wgmma.mma_async.sync.aligned.m64n72k16.f32.bf16.bf16 {%0, %1, %2, %3, %4, %5, %6, %7, %8, %9, %10, %11, %12, "
        "%13, %14, %15, %16, %17, %18, %19, %20, %21, %22, %23, %24, %25, %26, %27, %28, %29, %30, %31, %32, %33, %34, "
        "%35}, {%36, %37, %38, %39}, db, 1, 1, 1, 1;\n"
        "add.u32 b, %68, 4286578816;\nmov.b64 db, {b, 0x40000040};\n"
        "wgmma.mma_async.sync.aligned.m64n72k16.f32.bf16.bf16 {%0, %1, %2, %3, %4, %5, %6, %7, %8, %9, %10, %11, %12, "
        "%13, %14, %15, %16, %17, %18, %19, %20, %21, %22, %23, %24, %25, %26, %27, %28, %29, %30, %31, %32, %33, %34, "
        "%35}, {%40, %41, %42, %43}, db, 1, 1, 1, 1;\n"
        "add.u32 b, %68, 4278190336;\nmov.b64 db, {b, 0x40000040};\n"
        "wgmma.mma_async.sync.aligned.m64n72k16.f32.bf16.bf16 {%0, %1, %2, %3, %4, %5, %6, %7, %8, %9, %10, %11, %12, "
        "%13, %14, %15, %16, %17, %18, %19, %20, %21, %22, %23, %24, %25, %26, %27, %28, %29, %30, %31, %32, %33, %34, "
        "%35}, {%44, %45, %46, %47}, db, 1, 1, 1, 1;\n"
        "add.u32 b, %68, 4269801856;\nmov.b64 db, {b, 0x40000040};\n"
        "wgmma.mma_async.sync.aligned.m64n72k16.f32.bf16.bf16 {%0, %1, %2, %3, %4, %5, %6, %7, %8, %9, %10, %11, %12, "
        "%13, %14, %15, %16, %17, %18, %19, %20, %21, %22, %23, %24, %25, %26, %27, %28, %29, %30, %31, %32, %33, %34, "
        "%35}, {%48, %49, %50, %51}, db, 1, 1, 1, 1;\n"
        "add.u32 b, %68, 4261413376;\nmov.b64 db, {b, 0x40000040};\n"
        "wgmma.mma_async.sync.aligned.m64n72k16.f32.bf16.bf16 {%0, %1, %2, %3, %4, %5, %6, %7, %8, %9, %10, %11, %12, "
        "%13, %14, %15, %16, %17, %18, %19, %20, %21, %22, %23, %24, %25, %26, %27, %28, %29, %30, %31, %32, %33, %34, "
        "%35}, {%52, %53, %54, %55}, db, 1, 1, 1, 1;\n"
        "add.u32 b, %68, 4253024896;\nmov.b64 db, {b, 0x40000040};\n"
        "wgmma.mma_async.sync.aligned.m64n72k16.f32.bf16.bf16 {%0, %1, %2, %3, %4, %5, %6, %7, %8, %9, %10, %11, %12, "
        "%13, %14, %15, %16, %17, %18, %19, %20, %21, %22, %23, %24, %25, %26, %27, %28, %29, %30, %31, %32, %33, %34, "
        "%35}, {%56, %57, %58, %59}, db, 1, 1, 1, 1;\n"
        "add.u32 b, %68, 4244636416;\nmov.b64 db, {b, 0x40000040};\n"
        "wgmma.mma_async.sync.aligned.m64n72k16.f32.bf16.bf16 {%0, %1, %2, %3, %4, %5, %6, %7, %8, %9, %10, %11, %12, "
        "%13, %14, %15, %16, %17, %18, %19, %20, %21, %22, %23, %24, %25, %26, %27, %28, %29, %30, %31, %32, %33, %34, "
        "%35}, {%60, %61, %62, %63}, db, 1, 1, 1, 1;\n"
        "add.u32 b, %68, 4236247936;\nmov.b64 db, {b, 0x40000040};\n"
        "wgmma.mma_async.sync.aligned.m64n72k16.f32.bf16.bf16 {%0, %1, %2, %3, %4, %5, %6, %7, %8, %9, %10, %11, %12, "
        "%13, %14, %15, %16, %17, %18, %19, %20, %21, %22, %23, %24, %25, %26, %27, %28, %29, %30, %31, %32, %33, %34, "
        "%35}, {%64, %65, %66, %67}, db, 1, 1, 1, 1;\n"
        "wgmma.commit_group.sync.aligned;\n}"
        : "+f"(d[0]), "+f"(d[1]), "+f"(d[2]), "+f"(d[3]), "+f"(d[4]), "+f"(d[5]), "+f"(d[6]), "+f"(d[7]),
          "+f"(d[8]), "+f"(d[9]), "+f"(d[10]), "+f"(d[11]), "+f"(d[12]), "+f"(d[13]), "+f"(d[14]), "+f"(d[15]),
          "+f"(d[16]), "+f"(d[17]), "+f"(d[18]), "+f"(d[19]), "+f"(d[20]), "+f"(d[21]), "+f"(d[22]), "+f"(d[23]),
          "+f"(d[24]), "+f"(d[25]), "+f"(d[26]), "+f"(d[27]), "+f"(d[28]), "+f"(d[29]), "+f"(d[30]), "+f"(d[31]),
          "+f"(d[32]), "+f"(d[33]), "+f"(d[34]), "+f"(d[35])
        : "r"(a[0]), "r"(a[1]), "r"(a[2]), "r"(a[3]), "r"(a[4]), "r"(a[5]), "r"(a[6]), "r"(a[7]),
          "r"(a[8]), "r"(a[9]), "r"(a[10]), "r"(a[11]), "r"(a[12]), "r"(a[13]), "r"(a[14]), "r"(a[15]),
          "r"(a[16]), "r"(a[17]), "r"(a[18]), "r"(a[19]), "r"(a[20]), "r"(a[21]), "r"(a[22]), "r"(a[23]),
          "r"(a[24]), "r"(a[25]), "r"(a[26]), "r"(a[27]), "r"(a[28]), "r"(a[29]), "r"(a[30]), "r"(a[31]), "r"(b_lo) : "memory");
}

struct Ring {
    uint32_t slot, phase;
    __device__ __forceinline__ void next() { if (++slot == NSLOT) { slot = 0; phase ^= 1; } }
};

__device__ __forceinline__ void turn_wait(int wg) {
    asm volatile("bar.sync %0, 256;" :: "r"(wg + 1) : "memory");
}
__device__ __forceinline__ void turn_pass(int wg) {
    asm volatile("bar.arrive %0, 256;" :: "r"(wg == 2 ? 1 : wg + 2) : "memory");
}

__global__ void __cluster_dims__(2, 1, 1) __launch_bounds__(512, 1)
mha_kernel(const __grid_constant__ Params p) {
    extern __shared__ __align__(1024) uint8_t smem_raw[];
    const uint32_t sb = smem_u32(smem_raw);
    const uint32_t bar_full = sb + OFF_BAR, bar_empty = bar_full + 8 * NSLOT, bar_q = bar_empty + 8 * NSLOT;
    const uint32_t bar_item = bar_q + 24, bar_go = bar_item + 8;
    const uint32_t mailbox = bar_go + 8;
    const uint32_t rank = blockIdx.x & 1, cid = blockIdx.x >> 1;
    const int warp = __shfl_sync(0xffffffff, threadIdx.x >> 5, 0);
    const int wg = warp >> 2;
    const long long t_start = clock64();

    auto load_first_q = [&](uint32_t st) {
        while (clock64() - t_start < (int)(st >> 16) * 16) {}
        const int row = item_row0(st, rank);
        for (int w = 0; w < item_nact(st); w++) {
            mbar_expect_tx(bar_q + 8 * w, 32768);
            for (int c = 0; c < 4; c++)
                tma_load(sb + OFF_Q + (w * 4 + c) * 8192, &p.q, bar_q + 8 * w, c * 64, row + w * 64, policy_normal());
        }
    };
    constexpr uint32_t EARLY = (800 / 16) << 16;
    if (warp == 12) {
        if (elect_one()) {
            const uint32_t st = p.start[cid];
            for (int i = 0; i < 3; i++) mbar_init(bar_q + 8 * i, 1);
            mbar_init_fence();
            if (st < EARLY) load_first_q(st);
        }
    } else if (warp == 13) {
        if (elect_one()) {
            asm volatile("prefetch.tensormap [%0];" :: "l"(&p.q) : "memory");
            asm volatile("prefetch.tensormap [%0];" :: "l"(&p.k) : "memory");
            asm volatile("prefetch.tensormap [%0];" :: "l"(&p.v) : "memory");
            for (int i = 0; i < NSLOT; i++) mbar_init(bar_full + 8 * i, 1);
            mbar_init(bar_item, 1);
            mbar_init_fence();
        }
    } else if (warp == 14) {
        if (elect_one()) {
            for (int i = 0; i < NSLOT; i++) mbar_init(bar_empty + 8 * i, 6);
            mbar_init(bar_go, 1);
            mbar_init_fence();
        }
    } else if (threadIdx.x < 256) {
        reinterpret_cast<uint2*>(smem_raw + OFF_ONES)[threadIdx.x] = make_uint2(0x3F803F80u, 0x3F803F80u);
        asm volatile("fence.proxy.async.shared::cta;" ::: "memory");
    }
    __syncthreads();
    asm volatile("barrier.cluster.arrive.relaxed.aligned;" ::: "memory");

    if (wg == 3) {
        asm volatile("setmaxnreg.dec.sync.aligned.u32 32;");
        if (warp == 12) {
            uint32_t idx = cid, it = p.start[cid];
            if (it >= EARLY && elect_one()) load_first_q(it);
            __syncwarp();
            asm volatile("barrier.cluster.wait.aligned;" ::: "memory");
            Ring ring{0, 1};
            int q_next = 0, q_parts = 0, q_row = 0;
            for (uint32_t round = 0; idx < (uint32_t)p.n_items; round++) {
                const int kv0 = item_head(it) * S + rank * 64;
                const uint64_t pol_q = (int)idx >= p.ef_from ? policy_first() : policy_normal();
                const uint64_t pol_kv = item_nact(it) == 3 ? pol_q : policy_normal();
                const int s_item = (int)idx >= p.late_from ? 23 : 19;
                int col = 0, row = kv0;
                if (elect_one()) mbar_expect_tx(bar_item, 4);
                __syncwarp();
#pragma unroll 1
                for (int s = 0; s < 24; s++) {
                    const uint32_t fb = bar_full + 8 * ring.slot;
                    const uint32_t dst = sb + OFF_RING + ring.slot * SLOT_BYTES + rank * 8192;
                    const CUtensorMap* map = s < 12 ? &p.k : &p.v;
                    mbar_wait(bar_empty + 8 * ring.slot, ring.phase);
                    if (elect_one()) {
                        mbar_expect_tx(fb, SLOT_BYTES);
                        tma_load_mc(dst, map, fb, col, row, pol_kv);
                        if (s == s_item - 2 && rank == 0) mbar_arrive(bar_go);
                    }
                    __syncwarp();
                    if (s == s_item) {
                        mbar_wait(bar_item, round & 1);
                        idx = __shfl_sync(0xffffffff, lds_u32(mailbox + 4 * (round & 1)), 0);
                        if (idx < (uint32_t)p.n_items) {
                            it = p.item[idx];
                            q_next = 0;
                            q_parts = 2 * item_nact(it);
                            q_row = item_row0(it, rank);
                        }
                    }
                    if (q_next < q_parts) {
                        if (elect_one()) {
                            const int t = q_next;
                            const uint32_t qb = bar_q + 8 * (t >> 1), qd = sb + OFF_Q + t * 16384;
                            if (!(t & 1)) mbar_expect_tx(qb, 32768);
                            tma_load(qd, &p.q, qb, (t & 1) * 128, q_row + (t >> 1) * 64, pol_q);
                            tma_load(qd + 8192, &p.q, qb, (t & 1) * 128 + 64, q_row + (t >> 1) * 64, pol_q);
                        }
                        __syncwarp();
                        q_next++;
                    }
                    if (s < 11) { col = (col + 64) & 255; if (col == 0) row += 128; }
                    else if (s == 11) { col = 0; row = kv0 + 256; }
                    else if (row == kv0 + 256) row = kv0;
                    else if (row == kv0) row = kv0 + 128;
                    else { row = kv0 + 256; col += 64; }
                    ring.next();
                }
            }
            for (int i = 0; i < NSLOT; i++) {
                mbar_wait(bar_empty + 8 * ring.slot, ring.phase);
                ring.next();
            }
        } else {
            asm volatile("barrier.cluster.wait.aligned;" ::: "memory");
            if (warp == 13 && rank == 0) {
                if (elect_one()) {
                    if (cid == 0) {
                        g_drawn = 0;
                        asm volatile("st.release.gpu.global.u32 [%0], %1;" :: "l"(&g_ready), "r"(1) : "memory");
                    }
                    uint32_t ready = 0;
                    for (int i = 0; i < (1 << 24) && !ready; i++)
                        asm volatile("ld.acquire.gpu.global.u32 %0, [%1];" : "=r"(ready) : "l"(&g_ready) : "memory");
                    if (!ready) __trap();
                }
                __syncwarp();
                for (uint32_t round = 0;; round++) {
                    mbar_wait(bar_go, round & 1);
                    uint32_t idx = 0;
                    if (elect_one()) {
                        const uint32_t drawn = atomicAdd(&g_drawn, 1);
                        if (drawn == (uint32_t)p.n_items - 1) g_ready = 0;
                        idx = (gridDim.x >> 1) + drawn;
                        for (uint32_t r = 0; r < 2; r++)
                            asm volatile("st.async.shared::cluster.mbarrier::complete_tx::bytes.u32 [%0], %1, [%2];"
                                         :: "r"(map_to_cta(mailbox + 4 * (round & 1), r)), "r"(idx),
                                            "r"(map_to_cta(bar_item, r)) : "memory");
                    }
                    if (__any_sync(0xffffffff, idx >= (uint32_t)p.n_items)) break;
                }
            }
        }
    } else {
        asm volatile("setmaxnreg.inc.sync.aligned.u32 160;");
        asm volatile("barrier.cluster.wait.aligned;" ::: "memory");
        const int w4 = warp & 3;
        const bool rel = (threadIdx.x & 31) == 0 && w4 < 2;
        const uint32_t rel_bar = map_to_cta(bar_empty, w4 & 1);
        const uint32_t desc_q = desc_lo(sb + OFF_Q) + wg * 2048;
        const uint32_t desc_ring = desc_lo(sb + OFF_RING);
        const uint32_t desc_sum = (desc_ring & 0xFFFF) | (((OFF_ONES - OFF_RING) / 16) << 16);
        uint32_t qphase = 0;
        if (wg == 2) turn_pass(2);

        for (uint32_t round = 0;; round++) {
            uint32_t idx = cid;
            if (round > 0) {
                mbar_spin(bar_item, (round - 1) & 1);
                idx = __shfl_sync(0xffffffff, lds_u32(mailbox + 4 * ((round - 1) & 1)), 0);
                if (idx >= (uint32_t)p.n_items) break;
            }
            const uint32_t item = p.item[idx];
            if (wg >= item_nact(item)) {
                Ring ring{0, round & 1};
#pragma unroll 1
                for (int t = 0; t < 7; t++) {
                    turn_wait(wg);
                    turn_pass(wg);
#pragma unroll 1
                    for (int i = t < 3 ? 0 : 1; i < 4; i++) {
                        if (w4 < 2) mbar_spin(bar_full + 8 * ring.slot, ring.phase);
                        mbar_arrive_cluster(rel_bar + 8 * ring.slot, rel);
                        ring.next();
                    }
                }
                continue;
            }
            auto full_wait = [&](int st) { mbar_spin(bar_full + 8 * (st & 7), (round + (st >> 3)) & 1); };
            auto release = [&](int st) { mbar_arrive_cluster(rel_bar + 8 * (st & 7), rel); };
            uint32_t P[96];
            float m0, m1;
            mbar_spin(bar_q + 8 * wg, qphase);
            qphase ^= 1;
#pragma unroll
            for (int j = 0; j < 3; j++) {
                float s[64];
                full_wait(4 * j);
                turn_wait(wg);
#pragma unroll
                for (int c = 0; c < 4; c++) {
                    const int st = 4 * j + c;
                    if (c > 0) full_wait(st);
                    const uint32_t da = desc_q + c * 512, db = desc_ring + (st & 7) * (SLOT_BYTES / 16);
                    if (c == 0) qk_group_init(s, da, db); else qk_group_acc(s, da, db);
                    if (c == 3) turn_pass(wg);
                    if (c > 0) { wg_wait<1>(); release(st - 1); }
                }
                wg_wait<0>();
                fence_regs(s);
                release(4 * j + 3);

                auto row_max = [&](float& x0, float& x1) {
                    x0 = fmaxf(s[0], s[1]); x1 = fmaxf(s[2], s[3]);
#pragma unroll
                    for (int i = 1; i < 16; i++) {
                        x0 = fmaxf(x0, fmaxf(s[4 * i], s[4 * i + 1]));
                        x1 = fmaxf(x1, fmaxf(s[4 * i + 2], s[4 * i + 3]));
                    }
                    x0 = fmaxf(x0, __shfl_xor_sync(0xffffffff, x0, 1));
                    x1 = fmaxf(x1, __shfl_xor_sync(0xffffffff, x1, 1));
                    x0 = fmaxf(x0, __shfl_xor_sync(0xffffffff, x0, 2));
                    x1 = fmaxf(x1, __shfl_xor_sync(0xffffffff, x1, 2));
                    x0 *= SCALE_LOG2E; x1 *= SCALE_LOG2E;
                };
                if (j == 0) {
                    row_max(m0, m1);
                } else {
                    int i0 = max(__float_as_int(s[0]), __float_as_int(s[1]));
                    int i1 = max(__float_as_int(s[2]), __float_as_int(s[3]));
#pragma unroll
                    for (int i = 1; i < 16; i++) {
                        i0 = __vimax3_s32(i0, __float_as_int(s[4 * i]), __float_as_int(s[4 * i + 1]));
                        i1 = __vimax3_s32(i1, __float_as_int(s[4 * i + 2]), __float_as_int(s[4 * i + 3]));
                    }
                    const int lim0 = __float_as_int((m0 + LAZY_T) * (1.0f / SCALE_LOG2E));
                    const int lim1 = __float_as_int((m1 + LAZY_T) * (1.0f / SCALE_LOG2E));
                    if (__any_sync(0xffffffff, i0 > lim0 || i1 > lim1 || (lim0 | lim1) < 0)) {
                        float x0, x1;
                        row_max(x0, x1);
                        const float n0 = fmaxf(m0, x0), n1 = fmaxf(m1, x1);
                        const float f0 = ex2(m0 - n0), f1 = ex2(m1 - n1);
                        const uint32_t g0 = pack_bf16(f0, f0), g1 = pack_bf16(f1, f1);
#pragma unroll
                        for (int i = 0; i < 16 * j; i++) {
                            P[2 * i] = mul_bf16x2(P[2 * i], g0);
                            P[2 * i + 1] = mul_bf16x2(P[2 * i + 1], g1);
                        }
                        m0 = n0; m1 = n1;
                    }
                }
#pragma unroll
                for (int i = 0; i < 16; i++) {
                    P[32 * j + 2 * i] = exp_pack(s[4 * i], s[4 * i + 1], m0);
                    P[32 * j + 2 * i + 1] = exp_pack(s[4 * i + 2], s[4 * i + 3], m1);
                }
            }

            uint32_t tid; asm volatile("mov.u32 %0, %%tid.x;" : "=r"(tid));
            __nv_bfloat16* optr = p.o + (size_t)(item_row0(item, rank) + (tid >> 5) * 16 + ((tid & 31) >> 2)) * D + (tid & 3) * 8;
            const bool q0 = tid & 1, q1 = tid & 2;
            float inv0, inv1;
            auto store_o = [&](const float* o, int c) {
#pragma unroll
                for (int h = 0; h < 2; h++) {
                    const float inv = h ? inv1 : inv0;
#pragma unroll
                    for (int g = 0; g < 2; g++) {
                        uint32_t r[4];
#pragma unroll
                        for (int i = 0; i < 4; i++) r[i] = pack_bf16(o[16 * g + 4 * i + 2 * h] * inv, o[16 * g + 4 * i + 2 * h + 1] * inv);
                        quad_swap(r[0], r[1], q0, 1); quad_swap(r[2], r[3], q0, 1);
                        quad_swap(r[0], r[2], q1, 2); quad_swap(r[1], r[3], q1, 2);
                        *reinterpret_cast<uint4*>(optr + h * 8 * D + c * 64 + g * 32) = make_uint4(r[0], r[1], r[2], r[3]);
                    }
                }
            };

            {
                float o[36];
                full_wait(12);
                turn_wait(wg);
#pragma unroll
                for (int j = 0; j < 3; j++) {
                    const int st = 12 + j;
                    if (j > 0) full_wait(st);
                    const uint32_t db = desc_sum - (st & 7) * ((SLOT_BYTES / 16) * 65535u);
                    if (j == 0) pvsum_group_init(o, P + 64, db); else pvsum_group_acc(o, P + 32 * (j - 1), db);
                    if (j == 2) turn_pass(wg);
                    if (j > 0) { wg_wait<1>(); release(st - 1); }
                }
                wg_wait<0>();
                fence_regs(o);
                release(14);
                inv0 = rcp(o[32]); inv1 = rcp(o[34]);
                store_o(o, 0);
            }
#pragma unroll
            for (int c = 1; c < 4; c++) {
                float o[32];
                full_wait(12 + 3 * c);
                turn_wait(wg);
#pragma unroll
                for (int j = 0; j < 3; j++) {
                    const int st = 12 + 3 * c + j;
                    if (j > 0) full_wait(st);
                    const uint32_t db = desc_ring + (st & 7) * (SLOT_BYTES / 16);
                    if (j == 0) pv_group_init(o, P + 64, db); else pv_group_acc(o, P + 32 * (j - 1), db);
                    if (j == 2) turn_pass(wg);
                    if (j > 0) { wg_wait<1>(); release(st - 1); }
                }
                wg_wait<0>();
                fence_regs(o);
                release(14 + 3 * c);
                store_o(o, c);
            }
        }
        if (wg == 0) turn_wait(0);
    }
}

typedef CUresult (*EncodeFn)(CUtensorMap*, CUtensorMapDataType, cuuint32_t, void*, const cuuint64_t*, const cuuint64_t*,
                             const cuuint32_t*, const cuuint32_t*, CUtensorMapInterleave, CUtensorMapSwizzle,
                             CUtensorMapL2promotion, CUtensorMapFloatOOBfill);

void make_map(EncodeFn enc, CUtensorMap* m, const void* ptr) {
    cuuint64_t gdim[2] = {(cuuint64_t)D, (cuuint64_t)NH * S};
    cuuint64_t gstr[1] = {(cuuint64_t)D * 2};
    cuuint32_t box[2] = {64, 64};
    cuuint32_t estr[2] = {1, 1};
    enc(m, CU_TENSOR_MAP_DATA_TYPE_BFLOAT16, 2, const_cast<void*>(ptr), gdim, gstr, box, estr,
        CU_TENSOR_MAP_INTERLEAVE_NONE, CU_TENSOR_MAP_SWIZZLE_128B, CU_TENSOR_MAP_L2_PROMOTION_L2_128B,
        CU_TENSOR_MAP_FLOAT_OOB_FILL_NONE);
}


void build_schedule(Params& p, int n) {
    const int split_first = 8, split_last = 16;
    const int at_once = 16, spacing = 216;
    int k = 0;
    for (int h = 0; h < split_first; h++) p.item[k++] = (uint16_t)(h | 1 << 9 | 2 << 11);
    for (int h = 0; h < split_first; h++) p.item[k++] = (uint16_t)(h | 2 << 9);
    for (int h = split_first; h < NH - split_last; h++) p.item[k++] = (uint16_t)(h | 3 << 9);
    for (int h = NH - split_last; h < NH; h++) p.item[k++] = (uint16_t)(h | 2 << 9);
    for (int h = NH - split_last; h < NH; h++) p.item[k++] = (uint16_t)(h | 1 << 9 | 2 << 11);
    p.n_items = k;
    p.ef_from = k - 130;
    p.late_from = k - 96;
    for (int c = 0; c < n; c++)
        p.start[c] = p.item[c] | (uint32_t)((c > at_once ? c - at_once : 0) * spacing / 16) << 16;
}

}

extern "C" void kernel_launch(void* const* d_in, const int* in_sizes, int n_in, void* d_out, int out_size) {
    static EncodeFn enc = nullptr;
    static int ncl = 0;
    if (!enc) {
        void* fn = nullptr;
        cudaDriverEntryPointQueryResult qr;
        cudaGetDriverEntryPoint("cuTensorMapEncodeTiled", &fn, cudaEnableDefault, &qr);
        enc = (EncodeFn)fn;
        cudaFuncSetAttribute(mha_kernel, cudaFuncAttributeMaxDynamicSharedMemorySize, SMEM_BYTES);
        int dev = 0, sms = 0;
        cudaGetDevice(&dev);
        cudaDeviceGetAttribute(&sms, cudaDevAttrMultiProcessorCount, dev);
        ncl = sms / 2 < MAX_CL ? sms / 2 : MAX_CL;
    }
    Params p = {};
    make_map(enc, &p.q, d_in[0]);
    make_map(enc, &p.k, d_in[1]);
    make_map(enc, &p.v, d_in[2]);
    p.o = (__nv_bfloat16*)d_out;
    build_schedule(p, ncl);
    mha_kernel<<<2 * ncl, 512, SMEM_BYTES>>>(p);
}
```
